```python
import torch

def _softmax(x, axis=-1):
    return torch.softmax(x, dim=axis)

def _gelu(x):
    return torch.nn.functional.gelu(x, approximate='tanh')

def _silu(x):
    return torch.nn.functional.silu(x)

def _sigmoid(x):
    return torch.sigmoid(x)

def _layernorm(x, axis=-1, eps=1e-05):
    m = x.mean(dim=axis, keepdim=True)
    v = x.var(dim=axis, keepdim=True, unbiased=False)
    return (x - m) / torch.sqrt(v + eps)

def _scatter_add(tgt, idx, src, axis=0):
    return tgt.clone().index_add_(axis, idx, src)

def _segment_sum(src, seg, n):
    out = torch.zeros((n,) + src.shape[1:], dtype=src.dtype)
    return out.index_add_(0, seg, src)

def _pad(x, pw):
    flat = tuple((v for pair in reversed(pw) for v in pair))
    return torch.nn.functional.pad(x, flat)
kernel_name = 'adaLN_cond__ssm_conv_s4__geglu_ffn__prompt'

def setup_inputs():

    _w = lambda a: (lambda t: t.to(torch.bfloat16) if t.is_floating_point() else t)(torch.as_tensor(a))

    def _A_setup():
        B, L, D, N = (1, 2048, 512, 128)
        A_re = -(lambda _x: torch.exp(torch.as_tensor(_x)))((lambda *s: torch.randn(*s, dtype=torch.bfloat16) * 3.2)(D, N))
        A_im = torch.pi * (lambda *s: torch.randn(*s, dtype=torch.bfloat16) * 0.1)(D, N)
        B_re = (lambda *s: torch.randn(*s, dtype=torch.bfloat16) * 0.2)(D, N)
        B_im = (lambda *s: torch.randn(*s, dtype=torch.bfloat16) * 0.2)(D, N)
        C_re = (lambda *s: torch.randn(*s, dtype=torch.bfloat16) * 0.2)(D, N)
        C_im = (lambda *s: torch.randn(*s, dtype=torch.bfloat16) * 0.2)(D, N)
        log_dt = (lambda *s: torch.randn(*s, dtype=torch.bfloat16) * 0.1)(D) * 0.5 - 4.0
        Dskip = (lambda *s: torch.randn(*s, dtype=torch.bfloat16) * 0.1)(D)
        return {'u': _w((lambda *s: torch.randn(*s, dtype=torch.bfloat16) * 0.05)(B, L, D)), 'A_re': _w(A_re), 'A_im': _w(A_im), 'B_re': _w(B_re), 'B_im': _w(B_im), 'C_re': _w(C_re), 'C_im': _w(C_im), 'log_dt': _w(log_dt), 'Dskip': _w(Dskip)}
    _A_in = _A_setup()

    def _B_setup():
        B, S, D, F = (1, 2048, 512, 1792)
        return {'x': _w((lambda *s: torch.randn(*s, dtype=torch.bfloat16) * 0.05)(B, S, D)), 'w_gate': _w((lambda *s: torch.randn(*s, dtype=torch.bfloat16) * 0.05)(D, F)), 'w_up': _w((lambda *s: torch.randn(*s, dtype=torch.bfloat16) * 0.05)(D, F)), 'w_down': _w((lambda *s: torch.randn(*s, dtype=torch.bfloat16) * 0.05)(F, D))}
    _B_in = _B_setup()
    return {'A_u': _A_in['u'], 'A_A_re': _A_in['A_re'], 'A_A_im': _A_in['A_im'], 'A_B_re': _A_in['B_re'], 'A_B_im': _A_in['B_im'], 'A_C_re': _A_in['C_re'], 'A_C_im': _A_in['C_im'], 'A_log_dt': _A_in['log_dt'], 'A_Dskip': _A_in['Dskip'], 'B_x': _B_in['x'], 'B_w_gate': _B_in['w_gate'], 'B_w_up': _B_in['w_up'], 'B_w_down': _B_in['w_down'], 'c': _w((lambda *s: torch.randn(*s, dtype=torch.bfloat16) * 0.1)(1, 512) * 8.0), 'w_mod': _w((lambda *s: torch.randn(*s, dtype=torch.bfloat16) * 0.1)(512, 6 * 512) * 512 ** (-0.5) * 8.0)}

def reference(A_u, A_A_re, A_A_im, A_B_re, A_B_im, A_C_re, A_C_im, A_log_dt, A_Dskip, B_x, B_w_gate, B_w_up, B_w_down, c, w_mod):

    def _A_ref(u, A_re, A_im, B_re, B_im, C_re, C_im, log_dt, Dskip):
        Bsz, L, D = u.shape
        dt = torch.exp(log_dt)[:, None]
        A = A_re + 1j * A_im
        Bc = B_re + 1j * B_im
        Cc = C_re + 1j * C_im
        logdA = dt * A
        dB = dt * Bc
        l = (lambda x, dt: x.to(dt))(torch.arange(L), A_re.dtype)
        P = torch.exp(logdA[:, :, None] * l[None, None, :])
        K = torch.einsum('dn,dnl,dn->dl', Cc, P, dB).real
        L2 = 2 * L
        Kp = _pad(K, ((0, 0), (0, L)))
        up = (lambda x, *d: x.permute(*d))(u, 0, 2, 1)
        up = _pad(up, ((0, 0), (0, 0), (0, L)))
        Kf = (lambda x, axes=(-2, -1): torch.fft.rfft2(x.float(), dim=axes))(Kp[:, None, :], axes=(-2, -1))
        Uf = (lambda x, axes=(-2, -1): torch.fft.rfft2(x.float(), dim=axes))(up[:, :, None, :], axes=(-2, -1))
        Yf = Uf * Kf[None, :, :, :]
        y = (lambda x, s, axes=(-2, -1): torch.fft.irfft2(x, s=s, dim=axes).to(torch.bfloat16))(Yf, (1, L2), axes=(-2, -1))[:, :, 0, :L]
        y = (lambda x, *d: x.permute(*d))(y, 0, 2, 1) + u * Dskip[None, None, :]
        return y

    def _B_ref(x, w_gate, w_up, w_down):
        return _gelu(x @ w_gate) * (x @ w_up) @ w_down
    x = A_u
    mod = (_silu(c) @ w_mod).reshape(c.shape[0], 6, 1, -1)
    sa, ca, ga, sb, cb, gb = (mod[:, 0].clone(), mod[:, 1].clone(), mod[:, 2].clone(), mod[:, 3].clone(), mod[:, 4].clone(), mod[:, 5].clone())
    h = _layernorm(x, axis=-1) * (1 + ca) + sa
    x = x + ga * _A_ref(h, A_A_re, A_A_im, A_B_re, A_B_im, A_C_re, A_C_im, A_log_dt, A_Dskip)
    h = _layernorm(x, axis=-1) * (1 + cb) + sb
    x = x + gb * _B_ref(h, B_w_gate, B_w_up, B_w_down)
    return x
```

```cpp
#include <cuda_runtime.h>
#include <cuda_bf16.h>
#include <cuda.h>
#include <stdint.h>

typedef __nv_bfloat16 bf16;
#define SPIN_LIMIT (1 << 22)

__device__ unsigned long long g_stats[2048];
__device__ __align__(16) unsigned long long g_modp[3072 * 2];
__device__ float g_gb[512];
__device__ __align__(1024) unsigned char g_x1t[16 * 131072];
__device__ __align__(1024) unsigned char g_wp[128 * 28672];
__device__ __align__(16) float g_uv[4 * 8 * 896];
__device__ __align__(1024) unsigned char g_act[128 * 57344];
__device__ unsigned int g_flags[512];
constexpr int NCP = 4;
__device__ __align__(16) float g_st2[NCP * 4096];

#define TS(k, i)
#define TSP(k, i, t)
#define TSG(k, i)
#define TSP2(k, i, t)
__device__ __forceinline__ uint32_t smem_u32(const void* p) { return (uint32_t)__cvta_generic_to_shared(p); }
__device__ __forceinline__ uint32_t lds32(uint32_t a) { uint32_t v; asm volatile("ld.shared.b32 %0,[%1];" : "=r"(v) : "r"(a)); return v; }
__device__ __forceinline__ uint32_t lds32v(uint32_t a) { uint32_t v; asm volatile("ld.volatile.shared.b32 %0,[%1];" : "=r"(v) : "r"(a)); return v; }
__device__ __forceinline__ uint2 lds64(uint32_t a) { uint2 v; asm volatile("ld.shared.v2.b32 {%0,%1},[%2];" : "=r"(v.x), "=r"(v.y) : "r"(a)); return v; }
__device__ __forceinline__ uint32_t ldg32nc(const void* p) { uint32_t v; asm volatile("ld.global.nc.b32 %0,[%1];" : "=r"(v) : "l"(p)); return v; }
__device__ __forceinline__ float2 lds64f(uint32_t a) { float2 v; asm volatile("ld.shared.v2.f32 {%0,%1},[%2];" : "=f"(v.x), "=f"(v.y) : "r"(a)); return v; }
__device__ __forceinline__ float4 lds128f(uint32_t a) { float4 v; asm volatile("ld.shared.v4.f32 {%0,%1,%2,%3},[%4];" : "=f"(v.x), "=f"(v.y), "=f"(v.z), "=f"(v.w) : "r"(a)); return v; }
__device__ __forceinline__ uint4 lds128(uint32_t a) { uint4 v; asm volatile("ld.shared.v4.b32 {%0,%1,%2,%3},[%4];" : "=r"(v.x), "=r"(v.y), "=r"(v.z), "=r"(v.w) : "r"(a)); return v; }
__device__ __forceinline__ void sts128(uint32_t a, uint4 v) { asm volatile("st.shared.v4.b32 [%0],{%1,%2,%3,%4};" ::"r"(a), "r"(v.x), "r"(v.y), "r"(v.z), "r"(v.w) : "memory"); }
__device__ __forceinline__ void sts128f(uint32_t a, float x, float y, float z, float w) { asm volatile("st.shared.v4.f32 [%0],{%1,%2,%3,%4};" ::"r"(a), "f"(x), "f"(y), "f"(z), "f"(w) : "memory"); }
__device__ __forceinline__ void sts32(uint32_t a, uint32_t x) { asm volatile("st.shared.b32 [%0],%1;" ::"r"(a), "r"(x) : "memory"); }
__device__ __forceinline__ void sts32f(uint32_t a, float x) { asm volatile("st.shared.f32 [%0],%1;" ::"r"(a), "f"(x) : "memory"); }
__device__ __forceinline__ void sts64f(uint32_t a, float x, float y) { asm volatile("st.shared.v2.f32 [%0],{%1,%2};" ::"r"(a), "f"(x), "f"(y) : "memory"); }
__device__ __forceinline__ void sts16(uint32_t a, uint32_t x) { asm volatile("st.shared.b16 [%0],%1;" ::"r"(a), "h"((unsigned short)x) : "memory"); }
__device__ __forceinline__ uint32_t lds16(uint32_t a) { unsigned short v; asm volatile("ld.shared.b16 %0,[%1];" : "=h"(v) : "r"(a)); return v; }
__device__ __forceinline__ float bflo(uint32_t v) { return __uint_as_float(v << 16); }
__device__ __forceinline__ float bfhi(uint32_t v) { return __uint_as_float(v & 0xffff0000u); }
__device__ __forceinline__ float bf2f(bf16 v) { return __bfloat162float(v); }
__device__ __forceinline__ uint32_t pack2(float lo, float hi) { uint32_t r; asm("cvt.rn.bf16x2.f32 %0,%1,%2;" : "=r"(r) : "f"(hi), "f"(lo)); return r; }
__device__ __forceinline__ float rbf(float x) { return bflo(pack2(x, 0.f)); }
__device__ __forceinline__ void bar_sync(int id, int n) { asm volatile("bar.sync %0,%1;" ::"r"(id), "r"(n) : "memory"); }
__device__ __forceinline__ void bar_arrive(int id, int n) { asm volatile("bar.arrive %0,%1;" ::"r"(id), "r"(n) : "memory"); }
__device__ __forceinline__ uint4 ldg128nc(const void* p) { uint4 v; asm volatile("ld.global.nc.L1::no_allocate.v4.b32 {%0,%1,%2,%3},[%4];" : "=r"(v.x), "=r"(v.y), "=r"(v.z), "=r"(v.w) : "l"(p)); return v; }
__device__ __forceinline__ uint2 ldg64nc(const void* p) { uint2 v; asm volatile("ld.global.nc.L1::no_allocate.v2.b32 {%0,%1},[%2];" : "=r"(v.x), "=r"(v.y) : "l"(p)); return v; }
__device__ __forceinline__ void ldmx4(uint32_t& r0, uint32_t& r1, uint32_t& r2, uint32_t& r3, uint32_t a) { asm volatile("ldmatrix.sync.aligned.m8n8.x4.shared.b16 {%0,%1,%2,%3},[%4];" : "=r"(r0), "=r"(r1), "=r"(r2), "=r"(r3) : "r"(a)); }
__device__ __forceinline__ void ldmx4t(uint32_t& r0, uint32_t& r1, uint32_t& r2, uint32_t& r3, uint32_t a) { asm volatile("ldmatrix.sync.aligned.m8n8.x4.trans.shared.b16 {%0,%1,%2,%3},[%4];" : "=r"(r0), "=r"(r1), "=r"(r2), "=r"(r3) : "r"(a)); }
__device__ __forceinline__ void stmx4(uint32_t a, uint32_t r0, uint32_t r1, uint32_t r2, uint32_t r3) { asm volatile("stmatrix.sync.aligned.m8n8.x4.shared.b16 [%0],{%1,%2,%3,%4};" ::"r"(a), "r"(r0), "r"(r1), "r"(r2), "r"(r3) : "memory"); }
__device__ __forceinline__ void stmx4t(uint32_t a, uint32_t r0, uint32_t r1, uint32_t r2, uint32_t r3) { asm volatile("stmatrix.sync.aligned.m8n8.x4.trans.shared.b16 [%0],{%1,%2,%3,%4};" ::"r"(a), "r"(r0), "r"(r1), "r"(r2), "r"(r3) : "memory"); }
__device__ __forceinline__ void mma_bf16(float (&d)[4], uint32_t a0, uint32_t a1, uint32_t a2, uint32_t a3, uint32_t b0, uint32_t b1) {
  asm volatile("mma.sync.aligned.m16n8k16.row.col.f32.bf16.bf16.f32 {%0,%1,%2,%3},{%4,%5,%6,%7},{%8,%9},{%0,%1,%2,%3};"
               : "+f"(d[0]), "+f"(d[1]), "+f"(d[2]), "+f"(d[3]) : "r"(a0), "r"(a1), "r"(a2), "r"(a3), "r"(b0), "r"(b1));
}
__device__ __forceinline__ void mma_tf32(float (&d)[4], float a0, float a1, float a2, float a3, float b0, float b1) {
  asm volatile("mma.sync.aligned.m16n8k8.row.col.f32.tf32.tf32.f32 {%0,%1,%2,%3},{%4,%5,%6,%7},{%8,%9},{%0,%1,%2,%3};"
               : "+f"(d[0]), "+f"(d[1]), "+f"(d[2]), "+f"(d[3])
               : "r"(__float_as_uint(a0)), "r"(__float_as_uint(a1)), "r"(__float_as_uint(a2)), "r"(__float_as_uint(a3)), "r"(__float_as_uint(b0)), "r"(__float_as_uint(b1)));
}
__device__ __forceinline__ float2 cmul(float2 a, float2 b) { return make_float2(fmaf(a.x, b.x, -a.y * b.y), fmaf(a.x, b.y, a.y * b.x)); }
__device__ __forceinline__ float2 csqr(float2 a) { float u = a.x * a.y; return make_float2(fmaf(a.x, a.x, -a.y * a.y), u + u); }
__device__ __forceinline__ float ex2f(float x) { float r; asm("ex2.approx.ftz.f32 %0,%1;" : "=f"(r) : "f"(x)); return r; }
__device__ __forceinline__ float2 cexpv(float2 a, float v) { float e = ex2f(a.x * v), p = a.y * v; return make_float2(e * __cosf(p), e * __sinf(p)); }
__device__ __forceinline__ void mb_init(uint32_t b, int n) { asm volatile("mbarrier.init.shared::cta.b64 [%0],%1;" ::"r"(b), "r"(n) : "memory"); }
__device__ __forceinline__ void mb_arrive(uint32_t b) { asm volatile("mbarrier.arrive.shared::cta.b64 _,[%0];" ::"r"(b) : "memory"); }
__device__ __forceinline__ void mb_expect(uint32_t b, uint32_t bytes) { asm volatile("mbarrier.arrive.expect_tx.shared::cta.b64 _,[%0],%1;" ::"r"(b), "r"(bytes) : "memory"); }
__device__ __forceinline__ void mb_wait(uint32_t b, uint32_t ph) {
  uint32_t ok; int it = 0;
  do { asm volatile("{.reg .pred p; mbarrier.try_wait.parity.shared::cta.b64 p,[%1],%2; selp.u32 %0,1,0,p;}" : "=r"(ok) : "r"(b), "r"(ph) : "memory"); } while (!ok && ++it < SPIN_LIMIT);
}
__device__ __forceinline__ void bulk_g2s(uint32_t dst, const void* src, uint32_t bytes, uint32_t bar) {
  asm volatile("cp.async.bulk.shared::cluster.global.mbarrier::complete_tx::bytes [%0],[%1],%2,[%3];" ::"r"(dst), "l"(src), "r"(bytes), "r"(bar) : "memory");
}
__device__ __forceinline__ void tma2d(uint32_t dst, const CUtensorMap* tm, uint32_t bar, int c0, int c1) {
  asm volatile("cp.async.bulk.tensor.2d.shared::cluster.global.mbarrier::complete_tx::bytes [%0],[%1,{%3,%4}],[%2];" ::"r"(dst), "l"(tm), "r"(bar), "r"(c0), "r"(c1) : "memory");
}
__device__ __forceinline__ uint32_t mapa(uint32_t a, uint32_t rank) { uint32_t r; asm volatile("mapa.shared::cluster.u32 %0,%1,%2;" : "=r"(r) : "r"(a), "r"(rank)); return r; }
__device__ __forceinline__ void mb_wait_cl(uint32_t b, uint32_t ph) {
  uint32_t ok; int it = 0;
  do { asm volatile("{.reg .pred p; mbarrier.try_wait.parity.acquire.cluster.shared::cta.b64 p,[%1],%2; selp.u32 %0,1,0,p;}" : "=r"(ok) : "r"(b), "r"(ph) : "memory"); } while (!ok && ++it < SPIN_LIMIT);
}
__device__ __forceinline__ float poll_mod(int col, bool on = true) {
  unsigned long long s0, s1; int it = on ? 0 : SPIN_LIMIT;
  do { asm volatile("ld.relaxed.gpu.global.v2.b64 {%0,%1},[%2];" : "=l"(s0), "=l"(s1) : "l"(g_modp + 2 * col) : "memory"); }
  while (((s0 >> 32) == 0 || (s1 >> 32) == 0) && ++it < SPIN_LIMIT);
  return rbf(__uint_as_float((uint32_t)s0) + __uint_as_float((uint32_t)s1));
}
__device__ __forceinline__ void wg_fence() { asm volatile("wgmma.fence.sync.aligned;" ::: "memory"); }
__device__ __forceinline__ void wg_commit() { asm volatile("wgmma.commit_group.sync.aligned;" ::: "memory"); }
__device__ __forceinline__ void wg_wait0() { asm volatile("wgmma.wait_group.sync.aligned 0;" ::: "memory"); }
__device__ __forceinline__ uint64_t mkdesc(uint32_t addr, uint32_t lbo, uint32_t sbo, uint32_t sw) {
  return (uint64_t)((addr & 0x3ffff) >> 4) | ((uint64_t)(lbo >> 4) << 16) | ((uint64_t)(sbo >> 4) << 32) | ((uint64_t)sw << 62);
}
__device__ __forceinline__ void wg112_tk(float* d, uint64_t da, uint64_t db, int sc){
 asm volatile("{.reg .pred p; setp.ne.b32 p, %58, 0;\n wgmma.mma_async.sync.aligned.m64n112k16.f32.bf16.bf16 {%0,%1,%2,%3,%4,%5,%6,%7,%8,%9,%10,%11,%12,%13,%14,%15,%16,%17,%18,%19,%20,%21,%22,%23,%24,%25,%26,%27,%28,%29,%30,%31,%32,%33,%34,%35,%36,%37,%38,%39,%40,%41,%42,%43,%44,%45,%46,%47,%48,%49,%50,%51,%52,%53,%54,%55}, %56, %57, p, 1, 1, 1, 0;}"
 : "+f"(d[0]),"+f"(d[1]),"+f"(d[2]),"+f"(d[3]),"+f"(d[4]),"+f"(d[5]),"+f"(d[6]),"+f"(d[7]),"+f"(d[8]),"+f"(d[9]),"+f"(d[10]),"+f"(d[11]),"+f"(d[12]),"+f"(d[13]),"+f"(d[14]),"+f"(d[15]),"+f"(d[16]),"+f"(d[17]),"+f"(d[18]),"+f"(d[19]),"+f"(d[20]),"+f"(d[21]),"+f"(d[22]),"+f"(d[23]),"+f"(d[24]),"+f"(d[25]),"+f"(d[26]),"+f"(d[27]),"+f"(d[28]),"+f"(d[29]),"+f"(d[30]),"+f"(d[31]),"+f"(d[32]),"+f"(d[33]),"+f"(d[34]),"+f"(d[35]),"+f"(d[36]),"+f"(d[37]),"+f"(d[38]),"+f"(d[39]),"+f"(d[40]),"+f"(d[41]),"+f"(d[42]),"+f"(d[43]),"+f"(d[44]),"+f"(d[45]),"+f"(d[46]),"+f"(d[47]),"+f"(d[48]),"+f"(d[49]),"+f"(d[50]),"+f"(d[51]),"+f"(d[52]),"+f"(d[53]),"+f"(d[54]),"+f"(d[55])
 : "l"(da), "l"(db), "r"(sc));
}
__device__ __forceinline__ void wg112_rk(float* d, uint32_t a0,uint32_t a1,uint32_t a2,uint32_t a3, uint64_t db, int sc){
 asm volatile("{.reg .pred p; setp.ne.b32 p, %61, 0;\n wgmma.mma_async.sync.aligned.m64n112k16.f32.bf16.bf16 {%0,%1,%2,%3,%4,%5,%6,%7,%8,%9,%10,%11,%12,%13,%14,%15,%16,%17,%18,%19,%20,%21,%22,%23,%24,%25,%26,%27,%28,%29,%30,%31,%32,%33,%34,%35,%36,%37,%38,%39,%40,%41,%42,%43,%44,%45,%46,%47,%48,%49,%50,%51,%52,%53,%54,%55}, {%56,%57,%58,%59}, %60, p, 1, 1, 0;}"
 : "+f"(d[0]),"+f"(d[1]),"+f"(d[2]),"+f"(d[3]),"+f"(d[4]),"+f"(d[5]),"+f"(d[6]),"+f"(d[7]),"+f"(d[8]),"+f"(d[9]),"+f"(d[10]),"+f"(d[11]),"+f"(d[12]),"+f"(d[13]),"+f"(d[14]),"+f"(d[15]),"+f"(d[16]),"+f"(d[17]),"+f"(d[18]),"+f"(d[19]),"+f"(d[20]),"+f"(d[21]),"+f"(d[22]),"+f"(d[23]),"+f"(d[24]),"+f"(d[25]),"+f"(d[26]),"+f"(d[27]),"+f"(d[28]),"+f"(d[29]),"+f"(d[30]),"+f"(d[31]),"+f"(d[32]),"+f"(d[33]),"+f"(d[34]),"+f"(d[35]),"+f"(d[36]),"+f"(d[37]),"+f"(d[38]),"+f"(d[39]),"+f"(d[40]),"+f"(d[41]),"+f"(d[42]),"+f"(d[43]),"+f"(d[44]),"+f"(d[45]),"+f"(d[46]),"+f"(d[47]),"+f"(d[48]),"+f"(d[49]),"+f"(d[50]),"+f"(d[51]),"+f"(d[52]),"+f"(d[53]),"+f"(d[54]),"+f"(d[55])
 : "r"(a0),"r"(a1),"r"(a2),"r"(a3), "l"(db), "r"(sc));
}
__device__ __forceinline__ void wg128_rs(float* d, uint32_t a0,uint32_t a1,uint32_t a2,uint32_t a3, uint64_t db, int sc){
 asm volatile("{.reg .pred p; setp.ne.b32 p, %69, 0;\n wgmma.mma_async.sync.aligned.m64n128k16.f32.bf16.bf16 {%0,%1,%2,%3,%4,%5,%6,%7,%8,%9,%10,%11,%12,%13,%14,%15,%16,%17,%18,%19,%20,%21,%22,%23,%24,%25,%26,%27,%28,%29,%30,%31,%32,%33,%34,%35,%36,%37,%38,%39,%40,%41,%42,%43,%44,%45,%46,%47,%48,%49,%50,%51,%52,%53,%54,%55,%56,%57,%58,%59,%60,%61,%62,%63}, {%64,%65,%66,%67}, %68, p, 1, 1, 1;}"
 : "+f"(d[0]),"+f"(d[1]),"+f"(d[2]),"+f"(d[3]),"+f"(d[4]),"+f"(d[5]),"+f"(d[6]),"+f"(d[7]),"+f"(d[8]),"+f"(d[9]),"+f"(d[10]),"+f"(d[11]),"+f"(d[12]),"+f"(d[13]),"+f"(d[14]),"+f"(d[15]),"+f"(d[16]),"+f"(d[17]),"+f"(d[18]),"+f"(d[19]),"+f"(d[20]),"+f"(d[21]),"+f"(d[22]),"+f"(d[23]),"+f"(d[24]),"+f"(d[25]),"+f"(d[26]),"+f"(d[27]),"+f"(d[28]),"+f"(d[29]),"+f"(d[30]),"+f"(d[31]),"+f"(d[32]),"+f"(d[33]),"+f"(d[34]),"+f"(d[35]),"+f"(d[36]),"+f"(d[37]),"+f"(d[38]),"+f"(d[39]),"+f"(d[40]),"+f"(d[41]),"+f"(d[42]),"+f"(d[43]),"+f"(d[44]),"+f"(d[45]),"+f"(d[46]),"+f"(d[47]),"+f"(d[48]),"+f"(d[49]),"+f"(d[50]),"+f"(d[51]),"+f"(d[52]),"+f"(d[53]),"+f"(d[54]),"+f"(d[55]),"+f"(d[56]),"+f"(d[57]),"+f"(d[58]),"+f"(d[59]),"+f"(d[60]),"+f"(d[61]),"+f"(d[62]),"+f"(d[63])
 : "r"(a0),"r"(a1),"r"(a2),"r"(a3), "l"(db), "r"(sc));
}
__device__ __forceinline__ void wg128_kt(float* d, uint64_t da, uint64_t db, int sc){
 asm volatile("{.reg .pred p; setp.ne.b32 p, %66, 0;\n wgmma.mma_async.sync.aligned.m64n128k16.f32.bf16.bf16 {%0,%1,%2,%3,%4,%5,%6,%7,%8,%9,%10,%11,%12,%13,%14,%15,%16,%17,%18,%19,%20,%21,%22,%23,%24,%25,%26,%27,%28,%29,%30,%31,%32,%33,%34,%35,%36,%37,%38,%39,%40,%41,%42,%43,%44,%45,%46,%47,%48,%49,%50,%51,%52,%53,%54,%55,%56,%57,%58,%59,%60,%61,%62,%63}, %64, %65, p, 1, 1, 0, 1;}"
 : "+f"(d[0]),"+f"(d[1]),"+f"(d[2]),"+f"(d[3]),"+f"(d[4]),"+f"(d[5]),"+f"(d[6]),"+f"(d[7]),"+f"(d[8]),"+f"(d[9]),"+f"(d[10]),"+f"(d[11]),"+f"(d[12]),"+f"(d[13]),"+f"(d[14]),"+f"(d[15]),"+f"(d[16]),"+f"(d[17]),"+f"(d[18]),"+f"(d[19]),"+f"(d[20]),"+f"(d[21]),"+f"(d[22]),"+f"(d[23]),"+f"(d[24]),"+f"(d[25]),"+f"(d[26]),"+f"(d[27]),"+f"(d[28]),"+f"(d[29]),"+f"(d[30]),"+f"(d[31]),"+f"(d[32]),"+f"(d[33]),"+f"(d[34]),"+f"(d[35]),"+f"(d[36]),"+f"(d[37]),"+f"(d[38]),"+f"(d[39]),"+f"(d[40]),"+f"(d[41]),"+f"(d[42]),"+f"(d[43]),"+f"(d[44]),"+f"(d[45]),"+f"(d[46]),"+f"(d[47]),"+f"(d[48]),"+f"(d[49]),"+f"(d[50]),"+f"(d[51]),"+f"(d[52]),"+f"(d[53]),"+f"(d[54]),"+f"(d[55]),"+f"(d[56]),"+f"(d[57]),"+f"(d[58]),"+f"(d[59]),"+f"(d[60]),"+f"(d[61]),"+f"(d[62]),"+f"(d[63])
 : "l"(da), "l"(db), "r"(sc));
}

__device__ __forceinline__ void conv_rho(float (&acc)[16][4], const uint32_t (&F)[16][2], uint32_t pa){
  const uint32_t a0_0=lds32(pa+0), a0_1=lds32(pa+32), a0_2=lds32(pa-32+0), a0_3=lds32v(pa+0);
  const uint32_t a15_0=lds32(pa+7680), a15_1=lds32(pa+7712), a15_2=lds32(pa-32+7680), a15_3=lds32v(pa+7680);
  const uint32_t a1_0=lds32(pa+512), a1_1=lds32(pa+544), a1_2=lds32(pa-32+512), a1_3=lds32v(pa+512);
  const uint32_t a14_0=lds32(pa+7168), a14_1=lds32(pa+7200), a14_2=lds32(pa-32+7168), a14_3=lds32v(pa+7168);
  mma_bf16(acc[15], a0_0,a0_1,a0_2,a0_3, F[15][0],F[15][1]);
  mma_bf16(acc[0], a0_0,a0_1,a0_2,a0_3, F[0][0],F[0][1]);
  mma_bf16(acc[1], a0_0,a0_1,a0_2,a0_3, F[1][0],F[1][1]);
  mma_bf16(acc[2], a0_0,a0_1,a0_2,a0_3, F[2][0],F[2][1]);
  mma_bf16(acc[3], a0_0,a0_1,a0_2,a0_3, F[3][0],F[3][1]);
  mma_bf16(acc[4], a0_0,a0_1,a0_2,a0_3, F[4][0],F[4][1]);
  mma_bf16(acc[5], a0_0,a0_1,a0_2,a0_3, F[5][0],F[5][1]);
  mma_bf16(acc[6], a0_0,a0_1,a0_2,a0_3, F[6][0],F[6][1]);
  mma_bf16(acc[7], a0_0,a0_1,a0_2,a0_3, F[7][0],F[7][1]);
  mma_bf16(acc[8], a0_0,a0_1,a0_2,a0_3, F[8][0],F[8][1]);
  mma_bf16(acc[9], a0_0,a0_1,a0_2,a0_3, F[9][0],F[9][1]);
  mma_bf16(acc[10], a0_0,a0_1,a0_2,a0_3, F[10][0],F[10][1]);
  mma_bf16(acc[11], a0_0,a0_1,a0_2,a0_3, F[11][0],F[11][1]);
  mma_bf16(acc[12], a0_0,a0_1,a0_2,a0_3, F[12][0],F[12][1]);
  mma_bf16(acc[13], a0_0,a0_1,a0_2,a0_3, F[13][0],F[13][1]);
  mma_bf16(acc[14], a0_0,a0_1,a0_2,a0_3, F[14][0],F[14][1]);
  mma_bf16(acc[15], a15_0,a15_1,a15_2,a15_3, F[0][0],F[0][1]);
  const uint32_t a2_0=lds32(pa+1024), a2_1=lds32(pa+1056), a2_2=lds32(pa-32+1024), a2_3=lds32v(pa+1024);
  const uint32_t a13_0=lds32(pa+6656), a13_1=lds32(pa+6688), a13_2=lds32(pa-32+6656), a13_3=lds32v(pa+6656);
  mma_bf16(acc[1], a1_0,a1_1,a1_2,a1_3, F[0][0],F[0][1]);
  mma_bf16(acc[2], a1_0,a1_1,a1_2,a1_3, F[1][0],F[1][1]);
  mma_bf16(acc[3], a1_0,a1_1,a1_2,a1_3, F[2][0],F[2][1]);
  mma_bf16(acc[4], a1_0,a1_1,a1_2,a1_3, F[3][0],F[3][1]);
  mma_bf16(acc[14], a1_0,a1_1,a1_2,a1_3, F[13][0],F[13][1]);
  mma_bf16(acc[15], a1_0,a1_1,a1_2,a1_3, F[14][0],F[14][1]);
  mma_bf16(acc[5], a1_0,a1_1,a1_2,a1_3, F[4][0],F[4][1]);
  mma_bf16(acc[6], a1_0,a1_1,a1_2,a1_3, F[5][0],F[5][1]);
  mma_bf16(acc[7], a1_0,a1_1,a1_2,a1_3, F[6][0],F[6][1]);
  mma_bf16(acc[8], a1_0,a1_1,a1_2,a1_3, F[7][0],F[7][1]);
  mma_bf16(acc[9], a1_0,a1_1,a1_2,a1_3, F[8][0],F[8][1]);
  mma_bf16(acc[10], a1_0,a1_1,a1_2,a1_3, F[9][0],F[9][1]);
  mma_bf16(acc[11], a1_0,a1_1,a1_2,a1_3, F[10][0],F[10][1]);
  mma_bf16(acc[12], a1_0,a1_1,a1_2,a1_3, F[11][0],F[11][1]);
  mma_bf16(acc[13], a1_0,a1_1,a1_2,a1_3, F[12][0],F[12][1]);
  mma_bf16(acc[14], a14_0,a14_1,a14_2,a14_3, F[0][0],F[0][1]);
  mma_bf16(acc[15], a14_0,a14_1,a14_2,a14_3, F[1][0],F[1][1]);
  const uint32_t a3_0=lds32(pa+1536), a3_1=lds32(pa+1568), a3_2=lds32(pa-32+1536), a3_3=lds32v(pa+1536);
  const uint32_t a12_0=lds32(pa+6144), a12_1=lds32(pa+6176), a12_2=lds32(pa-32+6144), a12_3=lds32v(pa+6144);
  mma_bf16(acc[2], a2_0,a2_1,a2_2,a2_3, F[0][0],F[0][1]);
  mma_bf16(acc[3], a2_0,a2_1,a2_2,a2_3, F[1][0],F[1][1]);
  mma_bf16(acc[4], a2_0,a2_1,a2_2,a2_3, F[2][0],F[2][1]);
  mma_bf16(acc[13], a2_0,a2_1,a2_2,a2_3, F[11][0],F[11][1]);
  mma_bf16(acc[14], a2_0,a2_1,a2_2,a2_3, F[12][0],F[12][1]);
  mma_bf16(acc[15], a2_0,a2_1,a2_2,a2_3, F[13][0],F[13][1]);
  mma_bf16(acc[5], a2_0,a2_1,a2_2,a2_3, F[3][0],F[3][1]);
  mma_bf16(acc[6], a2_0,a2_1,a2_2,a2_3, F[4][0],F[4][1]);
  mma_bf16(acc[7], a2_0,a2_1,a2_2,a2_3, F[5][0],F[5][1]);
  mma_bf16(acc[8], a2_0,a2_1,a2_2,a2_3, F[6][0],F[6][1]);
  mma_bf16(acc[9], a2_0,a2_1,a2_2,a2_3, F[7][0],F[7][1]);
  mma_bf16(acc[10], a2_0,a2_1,a2_2,a2_3, F[8][0],F[8][1]);
  mma_bf16(acc[11], a2_0,a2_1,a2_2,a2_3, F[9][0],F[9][1]);
  mma_bf16(acc[12], a2_0,a2_1,a2_2,a2_3, F[10][0],F[10][1]);
  mma_bf16(acc[13], a13_0,a13_1,a13_2,a13_3, F[0][0],F[0][1]);
  mma_bf16(acc[14], a13_0,a13_1,a13_2,a13_3, F[1][0],F[1][1]);
  mma_bf16(acc[15], a13_0,a13_1,a13_2,a13_3, F[2][0],F[2][1]);
  const uint32_t a4_0=lds32(pa+2048), a4_1=lds32(pa+2080), a4_2=lds32(pa-32+2048), a4_3=lds32v(pa+2048);
  const uint32_t a11_0=lds32(pa+5632), a11_1=lds32(pa+5664), a11_2=lds32(pa-32+5632), a11_3=lds32v(pa+5632);
  mma_bf16(acc[3], a3_0,a3_1,a3_2,a3_3, F[0][0],F[0][1]);
  mma_bf16(acc[4], a3_0,a3_1,a3_2,a3_3, F[1][0],F[1][1]);
  mma_bf16(acc[12], a3_0,a3_1,a3_2,a3_3, F[9][0],F[9][1]);
  mma_bf16(acc[13], a3_0,a3_1,a3_2,a3_3, F[10][0],F[10][1]);
  mma_bf16(acc[14], a3_0,a3_1,a3_2,a3_3, F[11][0],F[11][1]);
  mma_bf16(acc[15], a3_0,a3_1,a3_2,a3_3, F[12][0],F[12][1]);
  mma_bf16(acc[5], a3_0,a3_1,a3_2,a3_3, F[2][0],F[2][1]);
  mma_bf16(acc[6], a3_0,a3_1,a3_2,a3_3, F[3][0],F[3][1]);
  mma_bf16(acc[7], a3_0,a3_1,a3_2,a3_3, F[4][0],F[4][1]);
  mma_bf16(acc[8], a3_0,a3_1,a3_2,a3_3, F[5][0],F[5][1]);
  mma_bf16(acc[9], a3_0,a3_1,a3_2,a3_3, F[6][0],F[6][1]);
  mma_bf16(acc[10], a3_0,a3_1,a3_2,a3_3, F[7][0],F[7][1]);
  mma_bf16(acc[11], a3_0,a3_1,a3_2,a3_3, F[8][0],F[8][1]);
  mma_bf16(acc[12], a12_0,a12_1,a12_2,a12_3, F[0][0],F[0][1]);
  mma_bf16(acc[13], a12_0,a12_1,a12_2,a12_3, F[1][0],F[1][1]);
  mma_bf16(acc[14], a12_0,a12_1,a12_2,a12_3, F[2][0],F[2][1]);
  mma_bf16(acc[15], a12_0,a12_1,a12_2,a12_3, F[3][0],F[3][1]);
  const uint32_t a5_0=lds32(pa+2560), a5_1=lds32(pa+2592), a5_2=lds32(pa-32+2560), a5_3=lds32v(pa+2560);
  const uint32_t a10_0=lds32(pa+5120), a10_1=lds32(pa+5152), a10_2=lds32(pa-32+5120), a10_3=lds32v(pa+5120);
  mma_bf16(acc[4], a4_0,a4_1,a4_2,a4_3, F[0][0],F[0][1]);
  mma_bf16(acc[11], a4_0,a4_1,a4_2,a4_3, F[7][0],F[7][1]);
  mma_bf16(acc[12], a4_0,a4_1,a4_2,a4_3, F[8][0],F[8][1]);
  mma_bf16(acc[13], a4_0,a4_1,a4_2,a4_3, F[9][0],F[9][1]);
  mma_bf16(acc[14], a4_0,a4_1,a4_2,a4_3, F[10][0],F[10][1]);
  mma_bf16(acc[15], a4_0,a4_1,a4_2,a4_3, F[11][0],F[11][1]);
  mma_bf16(acc[5], a4_0,a4_1,a4_2,a4_3, F[1][0],F[1][1]);
  mma_bf16(acc[6], a4_0,a4_1,a4_2,a4_3, F[2][0],F[2][1]);
  mma_bf16(acc[7], a4_0,a4_1,a4_2,a4_3, F[3][0],F[3][1]);
  mma_bf16(acc[8], a4_0,a4_1,a4_2,a4_3, F[4][0],F[4][1]);
  mma_bf16(acc[9], a4_0,a4_1,a4_2,a4_3, F[5][0],F[5][1]);
  mma_bf16(acc[10], a4_0,a4_1,a4_2,a4_3, F[6][0],F[6][1]);
  mma_bf16(acc[11], a11_0,a11_1,a11_2,a11_3, F[0][0],F[0][1]);
  mma_bf16(acc[12], a11_0,a11_1,a11_2,a11_3, F[1][0],F[1][1]);
  mma_bf16(acc[13], a11_0,a11_1,a11_2,a11_3, F[2][0],F[2][1]);
  mma_bf16(acc[14], a11_0,a11_1,a11_2,a11_3, F[3][0],F[3][1]);
  mma_bf16(acc[15], a11_0,a11_1,a11_2,a11_3, F[4][0],F[4][1]);
  const uint32_t a6_0=lds32(pa+3072), a6_1=lds32(pa+3104), a6_2=lds32(pa-32+3072), a6_3=lds32v(pa+3072);
  const uint32_t a9_0=lds32(pa+4608), a9_1=lds32(pa+4640), a9_2=lds32(pa-32+4608), a9_3=lds32v(pa+4608);
  mma_bf16(acc[10], a5_0,a5_1,a5_2,a5_3, F[5][0],F[5][1]);
  mma_bf16(acc[11], a5_0,a5_1,a5_2,a5_3, F[6][0],F[6][1]);
  mma_bf16(acc[12], a5_0,a5_1,a5_2,a5_3, F[7][0],F[7][1]);
  mma_bf16(acc[13], a5_0,a5_1,a5_2,a5_3, F[8][0],F[8][1]);
  mma_bf16(acc[14], a5_0,a5_1,a5_2,a5_3, F[9][0],F[9][1]);
  mma_bf16(acc[15], a5_0,a5_1,a5_2,a5_3, F[10][0],F[10][1]);
  mma_bf16(acc[5], a5_0,a5_1,a5_2,a5_3, F[0][0],F[0][1]);
  mma_bf16(acc[6], a5_0,a5_1,a5_2,a5_3, F[1][0],F[1][1]);
  mma_bf16(acc[7], a5_0,a5_1,a5_2,a5_3, F[2][0],F[2][1]);
  mma_bf16(acc[8], a5_0,a5_1,a5_2,a5_3, F[3][0],F[3][1]);
  mma_bf16(acc[9], a5_0,a5_1,a5_2,a5_3, F[4][0],F[4][1]);
  mma_bf16(acc[10], a10_0,a10_1,a10_2,a10_3, F[0][0],F[0][1]);
  mma_bf16(acc[11], a10_0,a10_1,a10_2,a10_3, F[1][0],F[1][1]);
  mma_bf16(acc[12], a10_0,a10_1,a10_2,a10_3, F[2][0],F[2][1]);
  mma_bf16(acc[13], a10_0,a10_1,a10_2,a10_3, F[3][0],F[3][1]);
  mma_bf16(acc[14], a10_0,a10_1,a10_2,a10_3, F[4][0],F[4][1]);
  mma_bf16(acc[15], a10_0,a10_1,a10_2,a10_3, F[5][0],F[5][1]);
  const uint32_t a7_0=lds32(pa+3584), a7_1=lds32(pa+3616), a7_2=lds32(pa-32+3584), a7_3=lds32v(pa+3584);
  const uint32_t a8_0=lds32(pa+4096), a8_1=lds32(pa+4128), a8_2=lds32(pa-32+4096), a8_3=lds32v(pa+4096);
  mma_bf16(acc[9], a6_0,a6_1,a6_2,a6_3, F[3][0],F[3][1]);
  mma_bf16(acc[10], a6_0,a6_1,a6_2,a6_3, F[4][0],F[4][1]);
  mma_bf16(acc[11], a6_0,a6_1,a6_2,a6_3, F[5][0],F[5][1]);
  mma_bf16(acc[12], a6_0,a6_1,a6_2,a6_3, F[6][0],F[6][1]);
  mma_bf16(acc[13], a6_0,a6_1,a6_2,a6_3, F[7][0],F[7][1]);
  mma_bf16(acc[14], a6_0,a6_1,a6_2,a6_3, F[8][0],F[8][1]);
  mma_bf16(acc[15], a6_0,a6_1,a6_2,a6_3, F[9][0],F[9][1]);
  mma_bf16(acc[6], a6_0,a6_1,a6_2,a6_3, F[0][0],F[0][1]);
  mma_bf16(acc[7], a6_0,a6_1,a6_2,a6_3, F[1][0],F[1][1]);
  mma_bf16(acc[8], a6_0,a6_1,a6_2,a6_3, F[2][0],F[2][1]);
  mma_bf16(acc[9], a9_0,a9_1,a9_2,a9_3, F[0][0],F[0][1]);
  mma_bf16(acc[10], a9_0,a9_1,a9_2,a9_3, F[1][0],F[1][1]);
  mma_bf16(acc[11], a9_0,a9_1,a9_2,a9_3, F[2][0],F[2][1]);
  mma_bf16(acc[12], a9_0,a9_1,a9_2,a9_3, F[3][0],F[3][1]);
  mma_bf16(acc[13], a9_0,a9_1,a9_2,a9_3, F[4][0],F[4][1]);
  mma_bf16(acc[14], a9_0,a9_1,a9_2,a9_3, F[5][0],F[5][1]);
  mma_bf16(acc[15], a9_0,a9_1,a9_2,a9_3, F[6][0],F[6][1]);
  mma_bf16(acc[8], a7_0,a7_1,a7_2,a7_3, F[1][0],F[1][1]);
  mma_bf16(acc[9], a7_0,a7_1,a7_2,a7_3, F[2][0],F[2][1]);
  mma_bf16(acc[10], a7_0,a7_1,a7_2,a7_3, F[3][0],F[3][1]);
  mma_bf16(acc[11], a7_0,a7_1,a7_2,a7_3, F[4][0],F[4][1]);
  mma_bf16(acc[12], a7_0,a7_1,a7_2,a7_3, F[5][0],F[5][1]);
  mma_bf16(acc[13], a7_0,a7_1,a7_2,a7_3, F[6][0],F[6][1]);
  mma_bf16(acc[14], a7_0,a7_1,a7_2,a7_3, F[7][0],F[7][1]);
  mma_bf16(acc[15], a7_0,a7_1,a7_2,a7_3, F[8][0],F[8][1]);
  mma_bf16(acc[7], a7_0,a7_1,a7_2,a7_3, F[0][0],F[0][1]);
  mma_bf16(acc[8], a8_0,a8_1,a8_2,a8_3, F[0][0],F[0][1]);
  mma_bf16(acc[9], a8_0,a8_1,a8_2,a8_3, F[1][0],F[1][1]);
  mma_bf16(acc[10], a8_0,a8_1,a8_2,a8_3, F[2][0],F[2][1]);
  mma_bf16(acc[11], a8_0,a8_1,a8_2,a8_3, F[3][0],F[3][1]);
  mma_bf16(acc[12], a8_0,a8_1,a8_2,a8_3, F[4][0],F[4][1]);
  mma_bf16(acc[13], a8_0,a8_1,a8_2,a8_3, F[5][0],F[5][1]);
  mma_bf16(acc[14], a8_0,a8_1,a8_2,a8_3, F[6][0],F[6][1]);
  mma_bf16(acc[15], a8_0,a8_1,a8_2,a8_3, F[7][0],F[7][1]);
}

constexpr int A_WM = 0;
constexpr int A_G = 32768;
constexpr int A_PK = A_G + 16384, PK_CS = 2064 * 4;
constexpr int A_H = A_PK + 4 * PK_CS, H_HS = 2240, H_CS = 4480;
constexpr int A_X = A_H + 4 * H_CS, X_HS = 2112, X_CS = 4240;
constexpr int A_XP = A_X + 4 * X_CS + 128, XP_CS = 2064;
constexpr int A_TAB = A_XP + 4 * XP_CS;
constexpr int A_WR = A_TAB + 61440;
constexpr int A_KV = A_TAB + 8 * 64 * 176, KV_CS = 1344;
constexpr int A_MV = A_KV + 4 * KV_CS;
constexpr int A_SC = A_MV + 64;
constexpr int A_SIL = A_SC + 1024;
constexpr int A_BAR = A_SIL + 2048;
constexpr int A_SMEM = A_BAR + 64 + 1024;
static_assert((A_XP - A_X) % 128 == 64 && A_TAB % 16 == 0 && A_SC % 16 == 0 && A_WR % 128 == 0, "layout");

#define PFW 10
#define EARLY(c) ((c) < 32)
__device__ __forceinline__ void conv_main(uint32_t sb, int ch, int par, int lane, int cta, bool on) {
  float acc[16][4];
#pragma unroll
  for (int i = 0; i < 16; i++) { acc[i][0] = acc[i][1] = acc[i][2] = acc[i][3] = 0.f; }
  const int g = lane >> 2, q = lane & 3;
  uint32_t pa = sb + A_PK + ch * PK_CS + (16 + g - 2 * q) * 4 + par * 256;
  uint32_t ha = sb + A_H + ch * H_CS + ((lane >> 3) & 1) * H_HS + (8 + 8 * (lane >> 4) + (lane & 7)) * 16 - par * 64;
#pragma unroll 1
  for (int rho = on ? 0 : 3; rho < 4; rho++) {
    TSP(0, 21 + rho, 0);
    uint32_t F[16][2];
#pragma unroll
    for (int m = 0; m < 16; m += 2) ldmx4(F[m][0], F[m][1], F[m + 1][0], F[m + 1][1], ha + m * 128);
    conv_rho(acc, F, pa);
    pa += 64; ha -= 16;
  }
  if (threadIdx.x == 0) TS(0, 7);
  const uint32_t xb = sb + A_TAB + ch * 8192 + lane * 16;
  if (par) {
#pragma unroll
    for (int i = 0; i < 8; i++) {
      sts128f(xb + 4096 + i * 512, acc[i][0], acc[i][1], acc[i][2], acc[i][3]);
      acc[i][0] = acc[i + 8][0]; acc[i][1] = acc[i + 8][1]; acc[i][2] = acc[i + 8][2]; acc[i][3] = acc[i + 8][3];
    }
  } else {
#pragma unroll
    for (int i = 0; i < 8; i++) sts128f(xb + i * 512, acc[i + 8][0], acc[i + 8][1], acc[i + 8][2], acc[i + 8][3]);
  }
  const int d = 4 * cta + ch, al = (lane & 15) >> 1, hf = lane & 1, j = 8 * par + (lane >> 4);
  const uint32_t xa = sb + A_X + ch * X_CS + ((lane >> 3) & 1) * X_HS + (8 * j + (lane & 7)) * 16;
  const uint32_t xr = sb + A_X + ch * X_CS + hf * X_HS + (8 * j + al) * 16;
  unsigned char* gp = g_x1t + j * 131072 + ((d >> 3) * 2 + (al >> 2)) * 1024 + (d & 7) * 128 + ((((al & 3) * 2 + hf) ^ (d & 7)) << 4);
  uint32_t r[16];
#pragma unroll
  for (int i = 0; i < 4; i++) ldmx4t(r[4 * i], r[4 * i + 1], r[4 * i + 2], r[4 * i + 3], xa + i * 256);
  if (on) mb_wait(sb + A_BAR + 32, 0);
  const float ga = __uint_as_float(lds32(sb + A_MV + (8 + ch) * 4));
#pragma unroll
  for (int i = 0; i < 8; i++) {
    acc[i][0] = fmaf(ga, acc[i][0], bflo(r[2 * i])); acc[i][1] = fmaf(ga, acc[i][1], bfhi(r[2 * i]));
    acc[i][2] = fmaf(ga, acc[i][2], bflo(r[2 * i + 1])); acc[i][3] = fmaf(ga, acc[i][3], bfhi(r[2 * i + 1]));
  }
  bar_sync(1 + ch, 64);
  float4 p[8];
#pragma unroll
  for (int i = 0; i < 8; i++) p[i] = lds128f(xb + (par ^ 1) * 4096 + i * 512);
#pragma unroll
  for (int i = 0; i < 8; i += 2)
    stmx4t(xa + i * 128, pack2(fmaf(ga, p[i].x, acc[i][0]), fmaf(ga, p[i].y, acc[i][1])), pack2(fmaf(ga, p[i].z, acc[i][2]), fmaf(ga, p[i].w, acc[i][3])),
           pack2(fmaf(ga, p[i + 1].x, acc[i + 1][0]), fmaf(ga, p[i + 1].y, acc[i + 1][1])), pack2(fmaf(ga, p[i + 1].z, acc[i + 1][2]), fmaf(ga, p[i + 1].w, acc[i + 1][3])));
  __syncwarp();
  uint4 v[4];
#pragma unroll
  for (int i = 0; i < 4; i++) v[i] = lds128(xr + i * 256);
#pragma unroll
  for (int i = 0; i < 4; i++)
    asm volatile("{.reg .pred p; setp.ne.b32 p,%5,0; @p st.global.v4.b32 [%0],{%1,%2,%3,%4};}" ::"l"(gp + i * 262144), "r"(v[i].x), "r"(v[i].y), "r"(v[i].z), "r"(v[i].w), "r"((int)on) : "memory");
}

__global__ void __launch_bounds__(512, 1) kernel_a(const __grid_constant__ CUtensorMap tm_x, const __grid_constant__ CUtensorMap tm_wm,
    const __grid_constant__ CUtensorMap tm_wg, const __grid_constant__ CUtensorMap tm_wu,
    const bf16* __restrict__ x, const bf16* __restrict__ Are, const bf16* __restrict__ Aim,
    const bf16* __restrict__ Bre, const bf16* __restrict__ Bim, const bf16* __restrict__ Cre, const bf16* __restrict__ Cim,
    const bf16* __restrict__ logdt, const bf16* __restrict__ dskip, const bf16* __restrict__ wd, const bf16* __restrict__ cvec, const bf16* __restrict__ wm) {
  extern __shared__ __align__(1024) unsigned char smem[];
  const uint32_t sb = (smem_u32(smem) + 1023) & ~1023u, bar = sb + A_BAR;
  const int tid = threadIdx.x, warp = tid >> 5, lane = tid & 31, rank = blockIdx.x & 1;
  const bool on = blockIdx.x < 128;
  const int cta = blockIdx.x & 127, sec = on ? -1 : cta;
  uint4 xa[4][2];
  if (warp < 8) {
    const int o = (4 * cta + (warp >> 1)) * 128 + (warp & 1) * 64 + 2 * lane;
    xa[0][0] = make_uint4(ldg32nc(Are + o), ldg32nc(Aim + o), ldg32nc(Bre + o), ldg32nc(Bim + o));
    xa[0][1] = make_uint4(ldg32nc(Cre + o), ldg32nc(Cim + o), ldg32nc(logdt + 4 * cta + (warp >> 2) * 2), ldg32nc(dskip + 4 * cta + (warp >> 2) * 2));
  } else if (warp < 12) {
#pragma unroll
    for (int r = 0; r < 4; r++) {
      const bf16* p = x + (size_t)(16 * cta + 4 * (warp - 8)) * 512 + (lane >> 2) * 128 + r * 32 + (lane & 3) * 8;
      xa[r][0] = ldg128nc(p); xa[r][1] = ldg128nc(p + 1024);
    }
  } else {
    const uint2 cr = ldg64nc(cvec + 4 * (tid - 384));
    xa[0][0].x = cr.x; xa[0][0].y = cr.y;
    if (EARLY(cta)) {
      const int r0 = (tid - 384) >> 3, ck = tid & 7;
      const bf16* p = wm + (size_t)(256 * rank + r0) * 3072 + 64 * (cta >> 1) + 8 * ck;
#pragma unroll
      for (int i = 0; i < 16; i++)
        asm volatile("cp.async.cg.shared.global [%0],[%1],16;" ::"r"(sb + A_WM + (r0 + 16 * i) * 128 + ((ck ^ (r0 & 7)) << 4)), "l"(p + i * 16 * 3072) : "memory");
    }
  }
  asm volatile("griddepcontrol.launch_dependents;");
  if (warp == 0) { TSG(0, 31); TS(0, 0); }
  if (tid == 416 && on) {
    mb_init(bar, 1); mb_init(bar + 8, 1); mb_init(bar + 16, 1); mb_init(bar + 24, 1); mb_init(bar + 32, 4);
    mb_expect(bar + 16, 8192);
    asm volatile("fence.mbarrier_init.release.cluster;" ::: "memory");
  }
  __syncwarp();
  asm volatile("barrier.cluster.arrive.relaxed.aligned;" ::: "memory");
  if (warp < 8) {
    const int ch = warp >> 1, par = warp & 1, g = lane >> 2, q = lane & 3;
    float prm[2][6];
    {
      const uint32_t w[6] = {xa[0][0].x, xa[0][0].y, xa[0][0].z, xa[0][0].w, xa[0][1].x, xa[0][1].y};
#pragma unroll
      for (int i = 0; i < 6; i++) { prm[0][i] = bflo(w[i]); prm[1][i] = bfhi(w[i]); }
    }
    const float ldt = (ch & 1) ? bfhi(xa[0][1].z) : bflo(xa[0][1].z), dsk = (ch & 1) ? bfhi(xa[0][1].w) : bflo(xa[0][1].w);
    if (tid < 4 && on) g_flags[4 * cta + tid] = 0;
    if (tid < 16) sts128(sb + A_PK + (tid >> 2) * PK_CS + (tid & 3) * 16, make_uint4(0, 0, 0, 0));
    if (tid >= 64 && tid < 128) { int u = tid - 64; sts128(sb + A_H + (u >> 4) * H_CS + ((u >> 3) & 1) * H_HS + (u & 7) * 16, make_uint4(0, 0, 0, 0)); }
    const uint32_t kv = sb + A_KV + ch * KV_CS;
    if (sec <= 0) {
    const float dt = rbf(expf(ldt));
    const uint32_t tab = sb + A_TAB + warp * 64 * 176;
    if (on) {
#pragma unroll
    for (int m = 0; m < 2; m++) {
      const float2 a = make_float2(dt * prm[m][0] * 1.4426950408889634f, dt * prm[m][1]);
      const float2 c = cmul(make_float2(prm[m][4], prm[m][5]), make_float2(dt * prm[m][2], dt * prm[m][3]));
      const float2 T2 = cexpv(a, 2.f), T64 = cexpv(a, 64.f), T4 = csqr(T2), T6 = cmul(T4, T2);
      const float2 T128 = csqr(T64), T192 = cmul(T128, T64), T256 = csqr(T128), T512 = csqr(T256), T768 = cmul(T512, T256);
      const float2 T1024 = csqr(T512), T1280 = cmul(T1024, T256), T1536 = cmul(T1024, T512), T1792 = cmul(T1024, T768), T2048 = csqr(T1024);
      const float2 T258 = cmul(T256, T2), T260 = cmul(T256, T4), T262 = cmul(T256, T6), T516 = cmul(T512, T4), T772 = cmul(T768, T4);
      const uint32_t e = tab + (lane + 32 * m) * 176;
      sts128f(e, a.x, a.y, c.x, c.y); sts128f(e + 16, T64.x, T64.y, T128.x, T128.y); sts128f(e + 32, T192.x, T192.y, 0.f, 0.f);
      sts128f(e + 48, T256.x, -T256.y, T258.x, -T258.y); sts128f(e + 64, T260.x, -T260.y, T262.x, -T262.y);
      sts128f(e + 80, T512.x, -T512.y, T516.x, -T516.y); sts128f(e + 96, T768.x, -T768.y, T772.x, -T772.y);
      sts128f(e + 112, T1024.x, -T1024.y, T1280.x, -T1280.y); sts128f(e + 128, T1536.x, -T1536.y, T1792.x, -T1792.y);
      sts128f(e + 144, T2048.x, -T2048.y, 0.f, 0.f);
    }
    }
    __syncwarp();
    if (warp == 0) TS(0, 1);
    float ka[2][3][4];
#pragma unroll
    for (int i = 0; i < 24; i++) (&ka[0][0][0])[i] = 0.f;
    const float gf = (float)g;
    const uint32_t q1o = 48 + g * 8, q2o = 112 + min(g, 4) * 8;
#pragma unroll 4
    for (int ks = on ? 0 : 12; ks < 16; ks++) {
      const uint32_t e = tab + (4 * ks + q) * 176;
      const float4 ac = lds128f(e), t1 = lds128f(e + 16);
      const float2 t3 = lds64f(e + 32), Q1 = lds64f(e + q1o), Q2 = lds64f(e + q2o);
      const float2 E1 = cexpv(make_float2(ac.x, ac.y), gf);
      const float2 E8 = csqr(csqr(csqr(E1)));
      const float2 P0 = cmul(E8, make_float2(ac.z, ac.w)), P1 = cmul(P0, make_float2(t1.x, t1.y)), P2 = cmul(P0, make_float2(t1.z, t1.w)), P3 = cmul(P0, t3);
      mma_tf32(ka[0][0], P0.x, P1.x, P0.y, P1.y, E1.x, -E1.y);
      mma_tf32(ka[1][0], P2.x, P3.x, P2.y, P3.y, E1.x, -E1.y);
      mma_tf32(ka[0][1], P0.x, P1.x, P0.y, P1.y, Q1.x, Q1.y);
      mma_tf32(ka[1][1], P2.x, P3.x, P2.y, P3.y, Q1.x, Q1.y);
      mma_tf32(ka[0][2], P0.x, P1.x, P0.y, P1.y, Q2.x, Q2.y);
      mma_tf32(ka[1][2], P2.x, P3.x, P2.y, P3.y, Q2.x, Q2.y);
    }
    if (warp == 0) TS(0, 2);
    __syncwarp();
#pragma unroll
    for (int i = 0; i < 12; i++) sts32f(tab + i * 128 + lane * 4, par ? (&ka[0][0][0])[i] : (&ka[1][0][0])[i]);
    bar_sync(1 + ch, 64);
    if (warp == 0) TS(0, 16);
    float pr[12];
#pragma unroll
    for (int i = 0; i < 12; i++) pr[i] = __uint_as_float(lds32(sb + A_TAB + (warp ^ 1) * 64 * 176 + i * 128 + lane * 4));
#pragma unroll
    for (int i = 0; i < 12; i++) {
      float v = (par ? (&ka[1][0][0])[i] : (&ka[0][0][0])[i]) + pr[i];
      const int nu = i >> 2, e = i & 3, row = 16 * par + g + 8 * (e >> 1), col = 2 * q + (e & 1);
      int idx;
      if (nu == 0) { idx = 8 * row + col; if (idx == 0) v += dsk; }
      else if (nu == 1) idx = (col < 4) ? 256 + col + 4 * row : 384 + 2 * row + (col & 1) + 64 * ((col - 4) >> 1);
      else idx = (col < 4) ? 512 + 32 * col + row : ((col == 4 && row == 0) ? 640 : -1);
      if (idx >= 0) sts16(kv + idx * 2, pack2(v, 0.f));
    }
    }
    if (on || sec == 1) {
    if (warp == 0) TS(0, 17);
    bar_sync(1 + ch, 64);
    if (warp == 0) TS(0, 18);
    {
      const uint32_t pk = sb + A_PK + ch * PK_CS + 64 + lane * 32;
      const uint32_t w4 = lds32(kv + 768 + par * 128 + lane * 4), v2 = lds16(kv + 772 + par * 128 + lane * 4);
      uint32_t v8[4];
#pragma unroll
      for (int i = 0; i < 4; i++) v8[i] = lds16(kv + 1024 + (i & 1) * 2 + par * 128 + (i >> 1) * 64 + lane * 2);
      if (par == 0) {
        const uint4 w = lds128(kv + lane * 16);
        const uint32_t m1 = lane ? lds16(kv + lane * 16 - 2) : 0u;
        sts128(pk, make_uint4(__byte_perm(w.x, m1, 0x5410), __byte_perm(w.x, 0, 0x1032), __byte_perm(w.y, w.x, 0x7610), __byte_perm(w.y, 0, 0x1032)));
        sts128(pk + 16, make_uint4(__byte_perm(w.z, w.y, 0x7610), __byte_perm(w.z, 0, 0x1032), __byte_perm(w.w, w.z, 0x7610), __byte_perm(w.w, 0, 0x1032)));
      } else {
        const uint2 w = lds64(kv + 512 + lane * 8);
        const uint32_t v4 = lds16(kv + 520 + lane * 8), m1 = lds16(kv + 512 + lane * 8 - (lane ? 0 : 2)), d2 = __byte_perm(w.y, 0, 0x1010);
        sts128(pk + 1024, make_uint4(__byte_perm(w.x, m1, 0x5410), __byte_perm(w.x, 0, 0x1010), __byte_perm(w.x, 0, 0x1032), __byte_perm(w.y, w.x, 0x7610)));
        sts128(pk + 1040, make_uint4(d2, d2, __byte_perm(w.y, 0, 0x1032), __byte_perm(v4, w.y, 0x7610)));
      }
      {
        const uint32_t w = w4;
        const uint32_t d0 = __byte_perm(w, 0, 0x1010), d1 = __byte_perm(w, 0, 0x3232);
        sts128(pk + 2048 + par * 1024, make_uint4(d0, d0, d0, __byte_perm(w, 0, 0x1032)));
        sts128(pk + 2064 + par * 1024, make_uint4(d1, d1, __byte_perm(v2, w, 0x7610), __byte_perm(v2, 0, 0x1010)));
      }
#pragma unroll
      for (int i = 0; i < 2; i++) {
        const uint32_t v0 = v8[2 * i], v1 = v8[2 * i + 1];
        const uint32_t d0 = __byte_perm(v0, 0, 0x1010), d1 = __byte_perm(v1, 0, 0x1010), e = __byte_perm(v1, v0, 0x5410);
        sts128(pk + 4096 + par * 2048 + i * 1024, make_uint4(d0, d0, d0, d0));
        sts128(pk + 4112 + par * 2048 + i * 1024, make_uint4((lane & 1) ? e : d0, (lane & 1) ? d1 : e, d1, d1));
      }
    }
    if (warp == 0) TS(0, 3);
    }
    if (on) bar_sync(6, 512);
    if (!on && sec != 2) return;
    if (warp == 0) TS(0, 6);
    conv_main(sb, ch, par, lane, cta, on);
    if (warp == 0) TS(0, 8);
    bar_sync(7, 256);
    float su[8], sq[8];
#pragma unroll
    for (int i = 0; i < 8; i++) su[i] = sq[i] = 0.f;
#pragma unroll
    for (int c = 0; c < 4; c++) {
      const uint4 xv = lds128(sb + A_X + c * X_CS + (tid & 1) * X_HS + (tid >> 1) * 16);
      const uint32_t xw[4] = {xv.x, xv.y, xv.z, xv.w};
#pragma unroll
      for (int i = 0; i < 4; i++) {
        const float lo = bflo(xw[i]), hi = bfhi(xw[i]);
        su[2 * i] += lo; su[2 * i + 1] += hi; sq[2 * i] = fmaf(lo, lo, sq[2 * i]); sq[2 * i + 1] = fmaf(hi, hi, sq[2 * i + 1]);
      }
    }
    float* sp = g_st2 + (cta & (NCP - 1)) * 4096 + tid * 4;
#pragma unroll
    for (int i = 0; i < 4; i++) {
      const float* v = (i < 2 ? su : sq) + (i & 1) * 4;
      asm volatile("{.reg .pred p; setp.ne.b32 p,%5,0; @p red.relaxed.gpu.global.add.v4.f32 [%0],{%1,%2,%3,%4};}" ::"l"(sp + i * 1024), "f"(v[0]), "f"(v[1]), "f"(v[2]), "f"(v[3]), "r"((int)on) : "memory");
    }
    if (warp == 0) { TS(0, 9); TSG(0, 30); }
  } else {
    const int t = tid & 127, w = warp & 3, g = lane >> 2, q = lane & 3;
    const int sl = cta >> 4, cc = (cta >> 2) & 3, kq = cta & 3;
    if (sec == 3) {
    } else if (warp < 12) {
      float c[6][4];
#pragma unroll
      for (int i = 0; i < 24; i++) (&c[0][0])[i] = 0.f;
#pragma unroll
      for (int r = 0; r < 4; r++) {
        const uint4 lo = xa[r][0], hi = xa[r][1];
        mma_bf16(c[0], lo.x, hi.x, lo.y, hi.y, lo.x, lo.y); mma_bf16(c[1], lo.x, hi.x, lo.y, hi.y, hi.x, hi.y); mma_bf16(c[2], lo.x, hi.x, lo.y, hi.y, 0x3f803f80u, 0x3f803f80u);
        mma_bf16(c[3], lo.z, hi.z, lo.w, hi.w, lo.z, lo.w); mma_bf16(c[4], lo.z, hi.z, lo.w, hi.w, hi.z, hi.w); mma_bf16(c[5], lo.z, hi.z, lo.w, hi.w, 0x3f803f80u, 0x3f803f80u);
      }
      const float ql = (g & 1) ? c[0][1] + c[3][1] : c[0][0] + c[3][0], qh = (g & 1) ? c[1][3] + c[4][3] : c[1][2] + c[4][2];
      const float q0 = __shfl_sync(~0u, ql, 4 * g + (g >> 1)), q1 = __shfl_sync(~0u, qh, 4 * g + (g >> 1));
      float sm = (lane & 1) ? c[2][2] + c[5][2] : c[2][0] + c[5][0], sq = (lane & 1) ? q1 : q0;
      sm += __shfl_xor_sync(~0u, sm, 4); sq += __shfl_xor_sync(~0u, sq, 4);
      sm += __shfl_xor_sync(~0u, sm, 8); sq += __shfl_xor_sync(~0u, sq, 8);
      const float mean = sm * (1.f / 512.f), ms = sq * (1.f / 512.f);
      if ((lane & 14) == 0 && on) {
        const float rs = rsqrtf(fmaxf(fmaf(-mean, mean, ms), 0.f) + 1e-5f);
        const unsigned long long pk = (unsigned long long)__float_as_uint(mean) | ((unsigned long long)(__float_as_uint(rs) | 1u) << 32);
        asm volatile("st.relaxed.gpu.global.b64 [%0],%1;" ::"l"(g_stats + 16 * cta + 4 * w + (lane >> 4) + 2 * (lane & 1)), "l"(pk) : "memory");
      }
      if (w == 0) TS(0, 10);
      bar_sync(5, 256);
    } else {
      {
        const float c0 = bflo(xa[0][0].x), c1 = bfhi(xa[0][0].x), c2 = bflo(xa[0][0].y), c3 = bfhi(xa[0][0].y);
        const uint32_t w0 = pack2(__fdividef(c0, 1.f + __expf(-c0)), __fdividef(c1, 1.f + __expf(-c1)));
        const uint32_t w1 = pack2(__fdividef(c2, 1.f + __expf(-c2)), __fdividef(c3, 1.f + __expf(-c3)));
        const uint32_t a = sb + A_SIL + (t >> 2) * 64 + (t & 1) * 32 + (t & 2) * 4;
        sts64f(a, __uint_as_float(w0), __uint_as_float(w0)); sts64f(a + 16, __uint_as_float(w1), __uint_as_float(w1));
      }
      asm volatile("cp.async.commit_group;" ::: "memory");
    {
      const bf16* p = x + (size_t)(1024 * rank + tid - 384) * 512 + 8 * (cta >> 1);
#pragma unroll
      for (int i = 0; i < 8; i++) asm volatile("cp.async.cg.shared.global [%0],[%1],16;" ::"r"(sb + A_G + (tid - 384 + 128 * i) * 16), "l"(p + i * 65536) : "memory");
    }
      asm volatile("cp.async.commit_group;" ::: "memory");
      bar_arrive(5, 256);
      asm volatile("cp.async.wait_group 1;" ::: "memory");
      bar_sync(10, 128);
    }
#pragma unroll 1
    for (int pass = 0; pass < 2 && sec != 3; pass++) {
    if (warp >= 12 && cta < 96 && EARLY(cta) == (pass == 0)) {
      {
        if (on && pass) mb_wait(bar + 8, 0);
        if (w == 0) TS(0, 12);
        float m[4][4];
#pragma unroll
        for (int i = 0; i < 16; i++) (&m[0][0])[i] = 0.f;
#pragma unroll
        for (int ks = 0; ks < 16; ks++) {
          uint32_t b0, b1, b2, b3;
          const int row = 16 * ks + (lane & 15);
          ldmx4t(b0, b1, b2, b3, sb + A_WM + row * 128 + (((2 * w + (lane >> 4)) ^ (row & 7)) << 4));
          const uint4 a = lds128(sb + A_SIL + rank * 1024 + ks * 64 + q * 16);
          mma_bf16(m[(ks & 1) * 2], a.x, a.y, a.z, a.w, b0, b1);
          mma_bf16(m[(ks & 1) * 2 + 1], a.x, a.y, a.z, a.w, b2, b3);
        }
        if (lane < 4 && on) {
#pragma unroll
          for (int i = 0; i < 4; i++) {
            const float v = m[i >> 1][i & 1] + m[2 + (i >> 1)][i & 1];
            asm volatile("st.relaxed.gpu.global.b64 [%0],%1;" ::"l"(g_modp + 2 * (64 * (cta >> 1) + 16 * w + 8 * (i >> 1) + 2 * q + (i & 1)) + rank),
                         "l"((unsigned long long)__float_as_uint(v) | (1ull << 32)) : "memory");
          }
        }
        if (w == 0) TS(0, 25);
      }
    }
    if (pass == 0) {
          if (warp >= 12) {
            asm volatile("cp.async.wait_all;" ::: "memory");
            bar_sync(10, 128);
            if (w == 0) TS(0, 11);
            const int c8 = lane & 7;
            const uint32_t dst = ((c8 >> 2) == rank) ? sb + A_X + (c8 & 3) * X_CS + ((lane >> 3) & 1) * X_HS + 1024 * rank
                                                      : sb + A_XP + (c8 & 3) * XP_CS + ((lane >> 3) & 1) * 1024;
#pragma unroll
            for (int h = 0; h < 2; h++) {
              uint32_t r[4][4];
#pragma unroll
              for (int i = 0; i < 4; i++) ldmx4t(r[i][0], r[i][1], r[i][2], r[i][3], sb + A_G + (32 * (8 * w + 4 * h + i) + lane) * 16);
#pragma unroll
              for (int i = 0; i < 4; i++) stmx4(dst + (2 * (8 * w + 4 * h + i) + (lane >> 4)) * 16, r[i][0], r[i][1], r[i][2], r[i][3]);
            }
            asm volatile("fence.proxy.async.shared::cta;" ::: "memory");
            bar_sync(11, 128);
            if (w == 1) {
              asm volatile("barrier.cluster.wait.acquire.aligned;" ::: "memory");
              if (lane < 8 && on)
                asm volatile("cp.async.bulk.shared::cluster.shared::cta.mbarrier::complete_tx::bytes [%0],[%1],%2,[%3];" ::"r"(mapa(sb + A_X + (lane >> 1) * X_CS + (lane & 1) * X_HS + 1024 * rank, rank ^ 1)),
                             "r"(sb + A_XP + (lane >> 1) * XP_CS + (lane & 1) * 1024), "r"(1024), "r"(mapa(bar + 16, rank ^ 1)) : "memory");
              __syncwarp();
            }
            if (tid == 448 && on && !EARLY(cta) && cta < 96) asm volatile("cp.async.bulk.prefetch.tensor.2d.L2.global [%0,{%1,%2}];" ::"l"(&tm_wm), "r"(64 * (cta >> 1)), "r"(256 * rank) : "memory");
            __syncwarp();
          }
      if (warp >= 12) bar_arrive(9, 256); else bar_sync(9, 256);
      const int hb = (lane >> 2) & 1, ho = (warp - 8) * 256 + (lane >> 3) * 16 + (lane & 3) * 4;
      ulonglong2 sv[5];
      const unsigned long long* gs = g_stats + 256 * (warp - 8) + 2 * lane;
      const unsigned long long* gm = g_modp + 2 * (((lane >> 2) & 1) * 512 + 4 * cta + (lane & 3));
      uint32_t xw[16];
#pragma unroll
      for (int i = 0; i < 5; i++) sv[i].x = sv[i].y = 0ull;
      for (int it = on ? 0 : SPIN_LIMIT, first = 1;; first = 0) {
        bool ok = true;
#pragma unroll
        for (int i = 0; i < 5; i++)
          asm volatile("{.reg .pred p; setp.ne.b32 p,%3,0; @p ld.relaxed.gpu.global.v2.b64 {%0,%1},[%2];}" : "+l"(sv[i].x), "+l"(sv[i].y)
                       : "l"(i < 4 ? gs + 64 * i : gm), "r"((int)((sv[i].x >> 32) == 0 || (sv[i].y >> 32) == 0)) : "memory");
        if (first) {
          if (on) mb_wait_cl(bar + 16, 0);
#pragma unroll
          for (int i = 0; i < 16; i++) xw[i] = lds32(sb + A_X + (i >> 2) * X_CS + hb * X_HS + ho + (i & 3) * 64);
        }
#pragma unroll
        for (int i = 0; i < 5; i++) ok = ok && (sv[i].x >> 32) != 0 && (sv[i].y >> 32) != 0;
        if (__all_sync(~0u, ok) || ++it >= SPIN_LIMIT) break;
      }
      float mv = rbf(__uint_as_float((uint32_t)sv[4].x) + __uint_as_float((uint32_t)sv[4].y));
      if (lane & 4) mv = rbf(1.f + mv);
      if (warp == 8) TS(0, 20);
      if (tid == 448 && on && !EARLY(cta) && cta < 96) { mb_expect(bar + 8, 32768); tma2d(sb + A_WM, &tm_wm, bar + 8, 64 * (cta >> 1), 256 * rank); }
      __syncwarp();
#pragma unroll
      for (int c = 0; c < 4; c++) {
        const float cc = __shfl_sync(~0u, mv, 4 + c), ss = __shfl_sync(~0u, mv, c);
#pragma unroll
        for (int i = 0; i < 4; i++) {
          sts32(sb + A_H + c * H_CS + hb * H_HS + 128 + ho + i * 64,
                pack2(fmaf((bflo(xw[4 * c + i]) - __uint_as_float((uint32_t)sv[i].x)) * __uint_as_float((uint32_t)(sv[i].x >> 32)), cc, ss),
                      fmaf((bfhi(xw[4 * c + i]) - __uint_as_float((uint32_t)sv[i].y)) * __uint_as_float((uint32_t)(sv[i].y >> 32)), cc, ss)));
        }
      }
      if (on) { if (warp < 10) bar_sync(6, 512); else bar_arrive(6, 512); }
      if (warp == PFW && lane == 0 && on) {
        asm volatile("cp.async.bulk.prefetch.tensor.2d.L2.global [%0,{%1,%2}];" ::"l"(&tm_wg), "r"(224 * sl + 56 * cc), "r"(128 * kq) : "memory");
        asm volatile("cp.async.bulk.prefetch.tensor.2d.L2.global [%0,{%1,%2}];" ::"l"(&tm_wu), "r"(224 * sl + 56 * cc), "r"(128 * kq) : "memory");
        asm volatile("cp.async.bulk.prefetch.L2.global [%0],%1;" ::"l"(reinterpret_cast<const char*>(wd) + cta * 14336), "r"(14336) : "memory");
      }
      __syncwarp();
      if (warp == 8) TS(0, 13);
    }
    }
    if (warp < 12 && sec != 3) {
      ulonglong2 pv[2];
      const unsigned long long* gm = g_modp + 2 * (3 * 512 + 128 * kq + t);
      for (int it = on ? 0 : SPIN_LIMIT;;) {
        bool ok = true;
#pragma unroll
        for (int i = 0; i < 2; i++) asm volatile("ld.relaxed.gpu.global.v2.b64 {%0,%1},[%2];" : "=l"(pv[i].x), "=l"(pv[i].y) : "l"(gm + 1024 * i) : "memory");
#pragma unroll
        for (int i = 0; i < 2; i++) ok = ok && (pv[i].x >> 32) != 0 && (pv[i].y >> 32) != 0;
        if (__all_sync(~0u, ok) || ++it >= SPIN_LIMIT) break;
      }
      if (warp == 8) TS(0, 4);
      if (t == 32 && on) {
        asm volatile("fence.proxy.async.shared::cta;" ::: "memory");
        mb_expect(bar + 24, 28672);
        tma2d(sb + A_WR, &tm_wg, bar + 24, 224 * sl + 56 * cc, 128 * kq);
        tma2d(sb + A_WR + 14336, &tm_wu, bar + 24, 224 * sl + 56 * cc, 128 * kq);
      }
      __syncwarp();
      float v[2];
#pragma unroll
      for (int i = 0; i < 2; i++) v[i] = rbf(__uint_as_float((uint32_t)pv[i].x) + __uint_as_float((uint32_t)pv[i].y));
      const uint32_t e = sb + A_SC + (t >> 4) * 64 + ((t >> 1) & 3) * 16 + (t & 1) * 2 + (t & 8);
      sts16(e, pack2(v[0], 0.f)); sts16(e + 4, pack2(1.f + v[1], 0.f));
    }
    if (!on && sec != 3) return;
    bar_sync(5, 256);
    if (on) mb_wait(bar + 24, 0);
    if (warp == 8) TS(0, 14);
    if (warp < 15) {
      float uv[2][2][4];
#pragma unroll
      for (int i = 0; i < 16; i++) (&uv[0][0][0])[i] = 0.f;
      const uint32_t src = sb + A_WR + lane * 112 + (warp - 8) * 16, dst = sb + A_TAB + 32768 + (lane >> 3) * 1792 + (warp - 8) * 256 + (lane & 7) * 16;
#pragma unroll
      for (int m = 0; m < 4; m++) {
        const uint4 a0 = lds128(sb + A_SC + m * 128 + q * 16), a1 = lds128(sb + A_SC + m * 128 + 64 + q * 16);
#pragma unroll
        for (int e = 0; e < 2; e++) {
          uint32_t r[4], p[4];
          ldmx4t(r[0], r[1], r[2], r[3], src + e * 14336 + m * 3584);
          asm("mul.rn.bf16x2 %0,%1,%2;" : "=r"(p[0]) : "r"(r[0]), "r"(a0.y));
          asm("mul.rn.bf16x2 %0,%1,%2;" : "=r"(p[1]) : "r"(r[1]), "r"(a0.w));
          asm("mul.rn.bf16x2 %0,%1,%2;" : "=r"(p[2]) : "r"(r[2]), "r"(a1.y));
          asm("mul.rn.bf16x2 %0,%1,%2;" : "=r"(p[3]) : "r"(r[3]), "r"(a1.w));
          stmx4(dst + e * 128 + m * 7168, p[0], p[1], p[2], p[3]);
          mma_bf16(uv[e][0], a0.x, a0.y, a0.z, a0.w, r[0], r[1]);
          mma_bf16(uv[e][1], a1.x, a1.y, a1.z, a1.w, r[2], r[3]);
        }
      }
      asm volatile("fence.proxy.async.shared::cta;" ::: "memory");
      if (g < 2 && on) {
        const int e = g;
        const float4 o = e ? make_float4(uv[1][0][2] + uv[1][1][2], uv[1][0][0] + uv[1][1][0], uv[1][0][3] + uv[1][1][3], uv[1][0][1] + uv[1][1][1])
                           : make_float4(uv[0][0][2] + uv[0][1][2], uv[0][0][0] + uv[0][1][0], uv[0][0][3] + uv[0][1][3], uv[0][0][1] + uv[0][1][1]);
        *reinterpret_cast<float4*>(g_uv + (kq * 8 + sl) * 896 + (cc * 112 + (2 * (warp - 8) + e) * 8 + 2 * q) * 2) = o;
      }
    }
    else if (lane < 8 && on) {
      const float v = poll_mod((lane < 4 ? 2 : 5) * 512 + 4 * cta + (lane & 3));
      if (lane < 4) { sts32f(sb + A_MV + 32 + lane * 4, v); mb_arrive(bar + 32); } else g_gb[4 * cta + (lane & 3)] = v;
    }
    __syncwarp();
    if (warp == 8) TS(0, 26);
    bar_sync(5, 256);
    if (warp == 8) TS(0, 27);
    if (tid == 256 && on) {
      asm volatile("cp.async.bulk.global.shared::cta.bulk_group [%0],[%1],%2;" ::"l"(g_wp + (size_t)cta * 28672), "r"(sb + A_TAB + 32768), "r"(28672) : "memory");
      asm volatile("cp.async.bulk.commit_group;" ::: "memory");
      asm volatile("cp.async.bulk.wait_group 0;" ::: "memory");
    }
    if (warp == 8) TS(0, 15);
  }
}

constexpr int STG = 28672, NDRY = 4;
constexpr int F_A = 0, F_RING = 131072, F_UV = F_RING + 3 * STG, F_GB = F_UV + 7168, F_RK = F_GB + 256, F_BAR = F_RK + 4096;
constexpr int F_SMEM = F_BAR + 1024 + 1024;
constexpr int B_FW = 0, B_EW = 24, B_FA = 48, B_UV = 80, B_AF = 88, B_FC = 160, B_AD = 192, B_PR = 216, B_XB = 224, B_F2 = 232, B_E2 = 264, STG2 = 21504;

#define mb_waitl(b, ph, lim) mb_wait((b) + lim, (ph) | dry)
__device__ __forceinline__ void bulk_p(uint32_t dst, const void* src, uint32_t bytes, uint32_t bar, int on) {
  asm volatile("{.reg .pred p; setp.ne.b32 p,%4,0;\n @p mbarrier.arrive.expect_tx.shared::cta.b64 _,[%3],%2;\n"
               "@p cp.async.bulk.shared::cluster.global.mbarrier::complete_tx::bytes [%0],[%1],%2,[%3];}" ::"r"(dst), "l"(src), "r"(bytes), "r"(bar), "r"(on) : "memory");
}
__device__ __forceinline__ void stg32_p(void* p, uint32_t v, int on) { asm volatile("{.reg .pred p; setp.ne.b32 p,%2,0; @p st.global.b32 [%0],%1;}" ::"l"(p), "r"(v), "r"(on) : "memory"); }
__device__ __forceinline__ void ldg32_p(uint32_t& v, const void* p, int on) { asm volatile("{.reg .pred p; setp.ne.b32 p,%2,0; mov.b32 %0,0; @p ld.global.b32 %0,[%1];}" : "=r"(v) : "l"(p), "r"(on) : "memory"); }
__device__ __forceinline__ void ldg64_p(uint32_t& v, uint32_t& w, const void* p, int on) {
  asm volatile("{.reg .pred p; setp.ne.b32 p,%3,0; mov.b32 %0,0; mov.b32 %1,0; @p ld.global.v2.b32 {%0,%1},[%2];}" : "=r"(v), "=r"(w) : "l"(p), "r"(on) : "memory");
}
__device__ __forceinline__ float tanh_ap(float x) { float r; asm("tanh.approx.f32 %0,%1;" : "=f"(r) : "f"(x)); return r; }
__device__ __forceinline__ float geglu(float a, float b, const float* k) {
  asm volatile("" : "+f"(a), "+f"(b));
  const float th = tanh_ap(a * fmaf(a * a, k[1], k[0]));
  return (a * b) * fmaf(th, k[2], k[2]);
}
template <int T0, int T1>
__device__ __forceinline__ void ffn_epi(const float* acc, uint32_t* act, unsigned char* gact, uint32_t rk, int on) {
  float kk[8];
  asm volatile("ld.volatile.shared.v4.f32 {%0,%1,%2,%3},[%4];" : "=f"(kk[0]), "=f"(kk[1]), "=f"(kk[2]), "=f"(kk[3]) : "r"(rk) : "memory");
  asm volatile("ld.volatile.shared.v4.f32 {%0,%1,%2,%3},[%4+256];" : "=f"(kk[4]), "=f"(kk[5]), "=f"(kk[6]), "=f"(kk[7]) : "r"(rk) : "memory");
#pragma unroll
  for (int t = T0; t < T1; t++) {
    act[2 * t] = pack2(geglu(acc[8 * t], acc[8 * t + 4], kk), geglu(acc[8 * t + 1], acc[8 * t + 5], kk));
    act[2 * t + 1] = pack2(geglu(acc[8 * t + 2], acc[8 * t + 6], kk + 4), geglu(acc[8 * t + 3], acc[8 * t + 7], kk + 4));
    stg32_p(gact + t * 2048, act[2 * t], on);
    stg32_p(gact + t * 2048 + 128, act[2 * t + 1], on);
  }
}
__device__ __forceinline__ void ln_row(float s, float ss, uint32_t dst) {
  const float nmu = s * (-1.f / 512.f), var = fmaxf(fmaf(ss, 1.f / 512.f, -nmu * nmu), 0.f) + 1e-5f, rs = rsqrtf(var), sg = var * rs;
  const float k2 = 0.5f * rs * rs, sh = rbf(sg), mh = rbf(nmu);
  sts128f(dst, 0.7978845608028654f * rs, 0.0713548162726f * rs * k2, k2, 0.f);
  sts128(dst + 16, make_uint4(pack2(sh, sg - sh), pack2(mh, nmu - mh), pack2(sh, mh), 0u));
}

__global__ void __launch_bounds__(384, 1) kernel_b(const __grid_constant__ CUtensorMap tm_wd, bf16* __restrict__ out) {
  extern __shared__ __align__(1024) unsigned char smem_raw[];
  const uint32_t sb = (smem_u32(smem_raw) + 1023) & ~1023u;
  const uint32_t bar = sb + F_BAR;
  const int tid = threadIdx.x, warp = __shfl_sync(~0u, tid >> 5, 0), lane = tid & 31;
  const int on = blockIdx.x >= NDRY, dry = !on, lim = dry * 512, cta = on ? blockIdx.x - NDRY : 0;
  const int kh = cta & 1, cq = (cta >> 1) & 3, rt = cta >> 3, sl = 4 * kh + cq;
  if (warp == 4) { TSG(1, 31); TS(1, 0); }
  if (tid == 0) {
    for (int i = 0; i < 3; i++) { mb_init(bar + B_FW + 8 * i, 1); mb_init(bar + B_EW + 8 * i, 8); mb_init(bar + B_AD + 8 * i, 8); }
    for (int i = 0; i < 4; i++) { mb_init(bar + B_FA + 8 * i, 1); mb_init(bar + B_FC + 8 * i, 1); mb_init(bar + B_F2 + 8 * i, 1); mb_init(bar + B_E2 + 8 * i, 8); }
    for (int i = 0; i < 9; i++) mb_init(bar + B_AF + 8 * i, 9);
    mb_init(bar + B_PR, 1); mb_init(bar + B_XB, 1); mb_init(bar + B_UV, 256);
    mb_expect(bar + B_XB, 16384);
    if (dry) for (int i = 0; i < 40; i++) mb_init(bar + 512 + 8 * i, 1);
    asm volatile("fence.mbarrier_init.release.cluster;" ::: "memory");
    asm volatile("prefetch.tensormap [%0];" ::"l"(&tm_wd) : "memory");
  }
  __syncthreads();
  asm volatile("barrier.cluster.arrive.relaxed.aligned;\n barrier.cluster.wait.acquire.aligned;" ::: "memory");
  const unsigned char* xs = g_x1t + (size_t)rt * 131072;
  const unsigned char* ws = g_wp + (size_t)sl * 16 * STG;
  if (warp < 4) {
    asm volatile("setmaxnreg.dec.sync.aligned.u32 40;");
    if (on) asm volatile("griddepcontrol.wait;" ::: "memory");
    if (warp == 0) {
      if (lane == 0) {
#pragma unroll
        for (int i = 0; i < 4; i++) {
          bulk_p(sb + F_A + i * 32768, xs + i * 32768, 32768, bar + B_FA + 8 * i, on);
          if (i < 3) bulk_p(sb + F_RING + i * STG, ws + i * STG, STG, bar + B_FW + 8 * i, on);
        }
        int slot = 0, ph = 0;
#pragma unroll 1
        for (int it = 3; it < 16; it++) {
          mb_waitl(bar + B_EW + 8 * slot, ph, lim);
          bulk_p(sb + F_RING + slot * STG, ws + it * STG, STG, bar + B_FW + 8 * slot, on);
          if (++slot == 3) { slot = 0; ph ^= 1; }
        }
        mb_waitl(bar + B_EW + 8, 0, lim);
#pragma unroll 1
        for (int j = 0; j < 13; j++) {
          const uint32_t s2 = (j + 2) & 3, fb = bar + B_F2 + 8 * s2, dst = sb + F_RING + s2 * STG2;
          mb_waitl(j < 2 ? bar + B_EW + 16 : j < 4 ? bar + B_EW : bar + B_E2 + 8 * s2, j < 4 ? j >> 1 : ((j >> 2) - 1) & 1, lim);
          if (j < 12) {
            const int p = (0xAA5404 >> 2 * j) & 3, row = 224 * (4 * kh + ((cq + (0xE4E790 >> 2 * j)) & 3)) + (p == 2 ? 144 : 80 * p);
            asm volatile("{.reg .pred p; setp.ne.b32 p,%6,0;\n @p mbarrier.arrive.expect_tx.shared::cta.b64 _,[%2],20480;\n"
                         "@p cp.async.bulk.tensor.2d.shared::cluster.global.mbarrier::complete_tx::bytes [%0],[%1,{%3,%5}],[%2];\n"
                         "@p cp.async.bulk.tensor.2d.shared::cluster.global.mbarrier::complete_tx::bytes [%0+10240],[%1,{%4,%5}],[%2];}"
                         ::"r"(dst), "l"(&tm_wd), "r"(fb), "r"(128 * cq + 64 * kh), "r"(128 * cq + 64 * (1 - kh)), "r"(row), "r"(on) : "memory");
          } else bulk_p(dst, xs + (2 * cq + kh) * 16384, 16384, fb, on);
        }
      }
    } else if (warp == 1) {
      if (lane == 0) {
#pragma unroll 1
        for (int n = 0, r = 1, p = 0; n < 9; n++) {
          mb_waitl(bar + B_AF + 8 * n, 0, lim);
          bulk_p(sb + F_A + (n & 3) * 32768, g_act + (size_t)(rt * 8 + 4 * kh + ((cq + r) & 3)) * 57344 + p * 20480, p == 2 ? 16384 : 20480, bar + B_FC + 8 * (n & 3), on);
          if (n == 3 && on) asm volatile("mbarrier.arrive.shared::cluster.b64 _,[%0];" ::"r"(mapa(bar + B_PR, kh ^ 1)) : "memory");
          if (++r == 4) { r = 1; p++; }
        }
      }
    } else if (on) {
      const int t = tid - 64;
      if (t < 16) g_stats[16 * cta + t] = 0ull;
      if (t >= 16) g_modp[48 * cta + t - 16] = 0ull;
      if (warp == 3) {
        const int p = lane / 3;
        const unsigned int* fp = g_flags + (rt * 8 + 4 * kh + ((cq + lane - 3 * p + 1) & 3)) * 4 + p;
        uint32_t f = lane >= 9;
        for (int it = 0; it < SPIN_LIMIT && !__all_sync(~0u, f); it++)
          if (!f) {
            asm volatile("ld.acquire.gpu.global.u32 %0,[%1];" : "=r"(f) : "l"(fp) : "memory");
            if (f) mb_arrive(bar + B_AF + 8 * lane);
          }
      }
      if (t == 0) {
#pragma unroll 1
        for (int p = 0; p < 3; p++) {
          mb_wait(bar + B_AD + 8 * p, 0);
          asm volatile("fence.proxy.async.global;" ::: "memory");
          asm volatile("fence.acq_rel.gpu;\n st.relaxed.gpu.global.u32 [%0],%1;" ::"l"(g_flags + (rt * 8 + sl) * 4 + p), "r"(1u) : "memory");
        }
      }
    }
  } else {
    asm volatile("setmaxnreg.inc.sync.aligned.u32 232;");
    const int wg = (warp >> 2) - 1, w4 = warp & 3, q = lane & 3;
    float acc[64], accB[56];
    uint32_t sav[56];
    uint32_t* const actA = sav + 28; uint32_t* const actB = sav + 42;
    const uint32_t rk = sb + F_RK + (wg * 64 + w4 * 16 + (lane >> 2)) * 32;
    uint32_t ex0 = 0u, ex1 = 0u, ez = 0u;
    const uint64_t dA = mkdesc(sb + F_A + wg * 1024, 0, 2048, 1);
    const uint64_t dW = mkdesc(sb + F_RING, 1792, 128, 0);
    const uint64_t dD = mkdesc(sb + F_RING, 10240, 1024, 1);
    const uint64_t dC = mkdesc(sb + F_A + wg * 1024, 2048, 128, 0);
    uint64_t dE = mkdesc(sb + F_UV, 0, 128, 0);
    unsigned char* gact = g_act + (size_t)(rt * 8 + sl) * 57344 + (wg * 8 + w4 * 2) * 128 + lane * 4;
    const uint32_t xoff = ((lane >> 4) * 2 + wg) * 1024 + (lane & 7) * 128 + (((2 * w4 + ((lane >> 3) & 1)) ^ (lane & 7)) << 4);
    uint32_t slot = 0, ph = 0;
    if (wg) bar_arrive(1, 256);
    const int ct = tid - 128, i1 = min(ct + 256, 447);
    {
      const float* pu = g_uv + sl * 896 + ct * 2;
      const float* pv = g_uv + sl * 896 + i1 * 2;
      const float* sp = g_st2 + ((ct >> 2) & 1) * 1024 + (16 * rt + ((ct & 127) >> 3)) * 4 + (ct & 3);
      const float* pg = g_gb + 128 * cq + 64 * kh + (ct & 63);
      asm volatile("" : "+l"(pu), "+l"(pv), "+l"(sp), "+l"(pg));
      if (on) asm volatile("griddepcontrol.wait;" ::: "memory");
      if (warp == 4) { TSG(1, 29); TS(1, 1); }
#pragma unroll
      for (int k = 0; k < 4; k++) {
        ldg64_p(sav[2 * k], sav[2 * k + 1], pu + k * 7168, on); ldg64_p(sav[8 + 2 * k], sav[9 + 2 * k], pv + k * 7168, on);
        ldg32_p(sav[16 + k], sp + k * 4096, on); ldg32_p(sav[20 + k], sp + k * 4096 + 2048, on);
      }
      ldg32_p(sav[24], pg, on);
    }
    mb_waitl(bar + B_FA, 0, lim); mb_waitl(bar + B_FW, 0, lim);
#pragma unroll 1
    for (int c = 0;; c += 2) {
      wg_wait0();
#pragma unroll
      for (int kq = 0; kq < 4; kq++) {
        const uint32_t eb = bar + B_EW + 8 * slot;
        if (c < 4) {
          bar_sync(1 + wg, 256);
          const uint32_t so = slot * (STG >> 4);
          TSP(1, 32 + 4 * (4 * c + kq), 128);
          if (kq == 3) { ex0 = lds32(rk + 16 + 4 * q); ex1 = lds32(rk + 272 + 4 * q); }
          wg_fence();
#pragma unroll
          for (int k = 0; k < 8; k++) wg112_tk(acc, dA + (uint64_t)((kq * 8 + k) * 256), dW + (uint64_t)(so + k * 224), (kq | k) != 0);
          if (kq == 3) wg112_rk(acc, ex0, ex1, ez, ez, dE, 1);
          wg_commit();
          bar_arrive(2 - wg, 256);
        }
        TSP2(1, 33 + 4 * (4 * c + kq), 128);
        if (c) {
          if (kq == 0) ffn_epi<0, 2>(accB, actB, gact, rk, on);
          if (kq == 1) ffn_epi<2, 4>(accB, actB, gact, rk, on);
          if (kq == 2) ffn_epi<4, 6>(accB, actB, gact, rk, on);
          if (kq == 3) { ffn_epi<6, 7>(accB, actB, gact, rk, on); gact += 14336; }
          if ((kq & 1) && c == kq + 1) { __syncwarp(); if (lane == 0) mb_arrive(bar + B_AD + 8 * kq - 8); }
        } else if (kq < 3) {
          if (kq == 1) {
            static_assert(NCP == 4, "");
            float f[25];
#pragma unroll
            for (int i = 0; i < 25; i++) f[i] = __uint_as_float(sav[i]);
#pragma unroll
            for (int j = 0; j < 2; j++) {
              const float u = (f[8 * j] + f[8 * j + 2]) + (f[8 * j + 4] + f[8 * j + 6]), v = (f[8 * j + 1] + f[8 * j + 3]) + (f[8 * j + 5] + f[8 * j + 7]);
              const float uh = rbf(u), vh = rbf(v);
              sts128(sb + F_UV + (j ? i1 : ct) * 16, make_uint4(pack2(vh, vh), pack2(uh, uh), pack2(v - vh, u - uh), 0u));
            }
            ln_row((f[16] + f[17]) + (f[18] + f[19]), (f[20] + f[21]) + (f[22] + f[23]), sb + F_RK + (ct & 127) * 32);
            sts32f(sb + F_GB + (ct & 63) * 4, f[24]);
            asm volatile("fence.proxy.async.shared::cta;" ::: "memory");
            mb_arrive(bar + B_UV);
          }
          mb_waitl(bar + B_FA + 8 * kq + 8, 0, lim);
          if (kq == 2) mb_waitl(bar + B_UV, 0, lim);
        }
        TSP2(1, 34 + 4 * (4 * c + kq), 128);
        if (c < 4) {
          if (kq == 3) {
#pragma unroll
            for (int i = 0; i < 14; i++) { sav[i] = actA[i]; sav[i + 14] = actB[i]; }
          }
          if (++slot == 3) { slot = 0; ph ^= 1; }
          mb_waitl(bar + B_FW + 8 * slot, ph, lim);
        }
        wg_wait0();
        TSP2(1, 35 + 4 * (4 * c + kq), 128);
        if (lane == 0 && c < 4) mb_arrive(eb);
      }
      if (c == 4) break;
      dE += 112;
#pragma unroll
      for (int kq = 0; kq < 4; kq++) {
        const uint32_t so = slot * (STG >> 4);
        bar_sync(1 + wg, 256);
        TSP(1, 48 + 4 * (4 * c + kq), 128);
        wg_fence();
#pragma unroll
        for (int k = 0; k < 8; k++) wg112_tk(accB, dA + (uint64_t)((kq * 8 + k) * 256), dW + (uint64_t)(so + k * 224), (kq | k) != 0);
        if (kq == 3) wg112_rk(accB, ex0, ex1, ez, ez, dE, 1);
        wg_commit();
        bar_arrive(2 - wg, 256);
        TSP2(1, 49 + 4 * (4 * c + kq), 128);
        if (kq == 0) ffn_epi<0, 2>(acc, actA, gact, rk, on);
        if (kq == 1) ffn_epi<2, 4>(acc, actA, gact, rk, on);
        if (kq == 2) { ffn_epi<4, 6>(acc, actA, gact, rk, on); if (c == 2) { __syncwarp(); if (lane == 0) mb_arrive(bar + B_AD + 8); } }
        if (kq == 3) ffn_epi<6, 7>(acc, actA, gact, rk, on);
        TSP2(1, 50 + 4 * (4 * c + kq), 128);
        const uint32_t eb = bar + B_EW + 8 * slot;
        if (++slot == 3) { slot = 0; ph ^= 1; }
        if (kq < 3 || c == 0) mb_waitl(bar + B_FW + 8 * slot, ph, lim);
        wg_wait0();
        TSP2(1, 51 + 4 * (4 * c + kq), 128);
        if (lane == 0) {
          mb_arrive(eb);
          if (c == 2) mb_arrive(bar + B_AF + 8 * kq);
        }
      }
      dE += 112; gact += 14336; c += 2 * dry;
    }
    slot = 2;
    mb_waitl(bar + B_F2 + 16, 0, lim);
    auto next = [&](int fc, int fp) {
      const uint32_t eb = bar + B_E2 + 8 * (slot & 3);
      slot++;
      mb_waitl(bar + B_F2 + 8 * (slot & 3), ((slot - 2) >> 2) & 1, lim);
      wg_wait0();
      if (lane == 0) { mb_arrive(eb); if (fc >= 1 && fc <= 5) mb_arrive(bar + B_AF + 24 + 8 * fc); }
      if (fp >= 0) mb_waitl(bar + B_FC + 8 * (fp & 3), (fp >> 2) & 1, lim);
    };
#define G2_OWN(K0, K1, OFF, TI)                                                                                                        \
    bar_sync(1 + wg, 256); TSP(1, TI, 128); wg_fence();                                                                                \
    _Pragma("unroll") for (int k = K0; k < K1; k++)                                                                                    \
      wg128_rs(acc, sav[4 * k], sav[4 * k + 1], sav[4 * k + 2], sav[4 * k + 3], dD + (uint64_t)((slot & 3) * (STG2 >> 4) + (k - OFF) * 128), k != 0); \
    wg_commit(); bar_arrive(2 - wg, 256);
#define G2_REM(N0, N1, KS, REL)                                                                                                        \
    _Pragma("unroll 1") for (int n = N0; n < N1; n++) {                                                                                \
      next(REL ? n : 0, n);                                                                                                            \
      bar_sync(1 + wg, 256); TSP(1, 5 - REL + n, 128); wg_fence();                                                                     \
      _Pragma("unroll") for (int k = 0; k < KS; k++)                                                                                   \
        wg128_kt(acc, dC + (uint64_t)((n & 3) * 2048 + k * 256), dD + (uint64_t)((slot & 3) * (STG2 >> 4) + (k + 5 - KS) * 128), 1);          \
      wg_commit(); bar_arrive(2 - wg, 256);                                                                                            \
    }
    G2_OWN(0, 5, 0, 2)
    next(0, -1);
    G2_OWN(5, 10, 5, 3)
    G2_REM(0, 6, 5, 1)
    next(0, -1);
    G2_OWN(10, 14, 9, 10)
    G2_REM(6, 9, 4, 0)
    if (!wg) bar_sync(1, 256);
    mb_waitl(bar + B_PR, 0, lim);
    wg_wait0();
    TSP(1, 16, 128);
    {
      const uint32_t ra = mapa(sb + F_A + STG + ct * 16, kh ^ 1), rb = mapa(bar + B_XB, kh ^ 1);
#pragma unroll
      for (int j = 0; j < 4; j++) {
        const float* a = acc + 32 + 8 * j;
        asm volatile("{.reg .pred p; setp.ne.b32 p,%6,0; @p st.async.weak.shared::cluster.mbarrier::complete_tx::bytes.v4.b32 [%0],{%1,%2,%3,%4},[%5];}" ::"r"(ra + j * 32768),
                     "r"(pack2(a[0], a[1])), "r"(pack2(a[2], a[3])), "r"(pack2(a[4], a[5])), "r"(pack2(a[6], a[7])), "r"(rb), "r"(on) : "memory");
      }
    }
    mb_waitl(bar + B_F2 + 16, 1, lim);
    float2 gv[8];
#pragma unroll
    for (int j = 0; j < 4; j++) {
      uint32_t r0, r1, r2, r3;
      ldmx4t(r0, r1, r2, r3, sb + F_RING + 2 * STG2 + j * 4096 + xoff);
      const float2 g0 = gv[2 * j] = lds64f(sb + F_GB + (16 * j + 2 * q) * 4), g1 = gv[2 * j + 1] = lds64f(sb + F_GB + (16 * j + 8 + 2 * q) * 4);
      float* a = acc + 8 * j;
      a[0] = fmaf(g0.x, a[0], bflo(r0)); a[1] = fmaf(g0.y, a[1], bfhi(r0)); a[2] = fmaf(g0.x, a[2], bflo(r1)); a[3] = fmaf(g0.y, a[3], bfhi(r1));
      a[4] = fmaf(g1.x, a[4], bflo(r2)); a[5] = fmaf(g1.y, a[5], bfhi(r2)); a[6] = fmaf(g1.x, a[6], bflo(r3)); a[7] = fmaf(g1.y, a[7], bfhi(r3));
    }
    asm volatile("" : "+f"(acc[0]), "+f"(acc[7]), "+f"(acc[8]), "+f"(acc[15]), "+f"(acc[16]), "+f"(acc[23]), "+f"(acc[24]), "+f"(acc[31]));
    mb_wait_cl(bar + B_XB + lim, dry);
    TSP(1, 17, 128);
    const uint32_t stg = sb + F_A + 2 * 32768 + (wg * 4 + w4) * 2048;
    uint4 p[4];
#pragma unroll
    for (int j = 0; j < 4; j++) p[j] = lds128(sb + F_A + STG + j * 32768 + ct * 16);
#pragma unroll
    for (int j = 0; j < 4; j++) {
      const float2 g0 = gv[2 * j], g1 = gv[2 * j + 1];
      const float* a = acc + 8 * j;
      const int row = (lane & 7) + 8 * ((lane >> 3) & 1);
      stmx4(stg + row * 128 + (((2 * j + (lane >> 4)) ^ (row & 7)) << 4),
            pack2(fmaf(g0.x, bflo(p[j].x), a[0]), fmaf(g0.y, bfhi(p[j].x), a[1])), pack2(fmaf(g0.x, bflo(p[j].y), a[2]), fmaf(g0.y, bfhi(p[j].y), a[3])),
            pack2(fmaf(g1.x, bflo(p[j].z), a[4]), fmaf(g1.y, bfhi(p[j].z), a[5])), pack2(fmaf(g1.x, bflo(p[j].w), a[6]), fmaf(g1.y, bfhi(p[j].w), a[7])));
    }
    __syncwarp();
#pragma unroll
    for (int i = 0; i < 4; i++) {
      const int row = 4 * i + (lane >> 3), ck = lane & 7;
      const uint4 v = lds128(stg + row * 128 + ((ck ^ (row & 7)) << 4));
      if (on) *reinterpret_cast<uint4*>(out + (size_t)(128 * rt + 64 * wg + 16 * w4 + row) * 512 + 128 * cq + 64 * kh + 8 * ck) = v;
    }
    if (warp == 11 && on) *reinterpret_cast<float4*>(g_st2 + (2 * sl + (lane >> 4)) * 1024 + (16 * rt + (lane & 15)) * 4) = make_float4(0.f, 0.f, 0.f, 0.f);
    if (warp == 4) { TS(1, 18); TSG(1, 30); }
  }
}

typedef CUresult (*EncodeFn)(CUtensorMap*, CUtensorMapDataType, cuuint32_t, void*, const cuuint64_t*, const cuuint64_t*, const cuuint32_t*, const cuuint32_t*,
                             CUtensorMapInterleave, CUtensorMapSwizzle, CUtensorMapL2promotion, CUtensorMapFloatOOBfill);

extern "C" void kernel_launch(void* const* d_in, const int* in_sizes, int n_in, void* d_out, int out_size) {
  static EncodeFn enc = nullptr;
  if (!enc) {
    void* fn = nullptr; cudaDriverEntryPointQueryResult qr;
    cudaGetDriverEntryPoint("cuTensorMapEncodeTiled", &fn, cudaEnableDefault, &qr);
    enc = (EncodeFn)fn;
    cudaFuncSetAttribute(kernel_a, cudaFuncAttributeMaxDynamicSharedMemorySize, A_SMEM);
    cudaFuncSetAttribute(kernel_b, cudaFuncAttributeMaxDynamicSharedMemorySize, F_SMEM);
  }
  const bf16* const* in = reinterpret_cast<const bf16* const*>(d_in);
  CUtensorMap tm, tm_x, tm_wm, tm_wg, tm_wu;
  auto mk = [&](CUtensorMap* m, void* p, unsigned cols, unsigned rows, unsigned bc, unsigned br, CUtensorMapSwizzle sw, CUtensorMapL2promotion pr) {
    cuuint64_t dims[2] = {cols, rows}, strides[1] = {cols * 2ull};
    cuuint32_t box[2] = {bc, br}, es[2] = {1, 1};
    enc(m, CU_TENSOR_MAP_DATA_TYPE_BFLOAT16, 2, p, dims, strides, box, es, CU_TENSOR_MAP_INTERLEAVE_NONE, sw, pr, CU_TENSOR_MAP_FLOAT_OOB_FILL_NONE);
  };
  mk(&tm, d_in[12], 512, 1792, 64, 80, CU_TENSOR_MAP_SWIZZLE_128B, CU_TENSOR_MAP_L2_PROMOTION_L2_128B);
  mk(&tm_x, d_in[0], 512, 2048, 8, 256, CU_TENSOR_MAP_SWIZZLE_NONE, CU_TENSOR_MAP_L2_PROMOTION_NONE);
  mk(&tm_wm, d_in[14], 3072, 512, 64, 256, CU_TENSOR_MAP_SWIZZLE_128B, CU_TENSOR_MAP_L2_PROMOTION_L2_128B);
  mk(&tm_wg, d_in[10], 1792, 512, 56, 128, CU_TENSOR_MAP_SWIZZLE_NONE, CU_TENSOR_MAP_L2_PROMOTION_NONE);
  mk(&tm_wu, d_in[11], 1792, 512, 56, 128, CU_TENSOR_MAP_SWIZZLE_NONE, CU_TENSOR_MAP_L2_PROMOTION_NONE);
  cudaLaunchConfig_t cfg = {};
  cfg.gridDim = dim3(132); cfg.blockDim = dim3(512); cfg.dynamicSmemBytes = A_SMEM; cfg.stream = cudaStreamPerThread;
  cudaLaunchAttribute at[2];
  at[0].id = cudaLaunchAttributeClusterDimension; at[0].val.clusterDim.x = 2; at[0].val.clusterDim.y = 1; at[0].val.clusterDim.z = 1;
  at[1].id = cudaLaunchAttributeProgrammaticStreamSerialization; at[1].val.programmaticStreamSerializationAllowed = 1;
  cfg.attrs = at; cfg.numAttrs = 1;
  cudaLaunchKernelEx(&cfg, kernel_a, tm_x, tm_wm, tm_wg, tm_wu, in[0], in[1], in[2], in[3], in[4], in[5], in[6], in[7], in[8], in[12], in[13], in[14]);
  cfg.dynamicSmemBytes = F_SMEM; cfg.blockDim = dim3(384); cfg.numAttrs = 2; cfg.gridDim = dim3(128 + NDRY);
  cudaLaunchKernelEx(&cfg, kernel_b, tm, (bf16*)d_out);
}
```
